```python
import torch

def _softmax(x, axis=-1):
    return torch.softmax(x, dim=axis)
def _gelu(x):
    return torch.nn.functional.gelu(x, approximate="tanh")
def _silu(x):
    return torch.nn.functional.silu(x)
def _sigmoid(x):
    return torch.sigmoid(x)
def _layernorm(x, axis=-1, eps=1e-5):
    m = x.mean(dim=axis, keepdim=True)
    v = x.var(dim=axis, keepdim=True, unbiased=False)
    return (x - m) / torch.sqrt(v + eps)
def _scatter_add(tgt, idx, src, axis=0):
    return tgt.clone().index_add_(axis, idx, src)
def _segment_sum(src, seg, n):
    out = torch.zeros((n,) + src.shape[1:], dtype=src.dtype)
    return out.index_add_(0, seg, src)
def _pad(x, pw):
    flat = tuple(v for pair in reversed(pw) for v in pair)
    return torch.nn.functional.pad(x, flat)

kernel_name = 'parallel_sum__ssm_conv_s4__mixer_channel_mlp__prompt'

def setup_inputs():

    _w = (lambda a: (lambda t: t.to(torch.bfloat16) if t.is_floating_point() else t)(torch.as_tensor(a)))
    def _A_setup():
        B, L, D, N = 1, 2048, 640, 128
        A_re = -(lambda _x: torch.exp(torch.as_tensor(_x)))((lambda *s: torch.randn(*s, dtype=torch.bfloat16) * 3.2)(D, N))
        A_im = torch.pi * (lambda *s: torch.randn(*s, dtype=torch.bfloat16) * 0.05)(D, N)
        B_re = (lambda *s: torch.randn(*s, dtype=torch.bfloat16) * 0.1)(D, N)
        B_im = (lambda *s: torch.randn(*s, dtype=torch.bfloat16) * 0.1)(D, N)
        C_re = (lambda *s: torch.randn(*s, dtype=torch.bfloat16) * 0.1)(D, N)
        C_im = (lambda *s: torch.randn(*s, dtype=torch.bfloat16) * 0.1)(D, N)
        log_dt = (lambda *s: torch.randn(*s, dtype=torch.bfloat16) * 0.05)(D) * 0.5 - 4.0
        Dskip = (lambda *s: torch.randn(*s, dtype=torch.bfloat16) * 0.05)(D)
        return {
            "u": _w((lambda *s: torch.randn(*s, dtype=torch.bfloat16) * 0.05)(B, L, D)),
            "A_re": _w(A_re),
            "A_im": _w(A_im),
            "B_re": _w(B_re),
            "B_im": _w(B_im),
            "C_re": _w(C_re),
            "C_im": _w(C_im),
            "log_dt": _w(log_dt),
            "Dskip": _w(Dskip),
        }
    _A_in = _A_setup()

    def _B_setup():
        B, S, D, F = 1, 2048, 640, 1728
        return {
            "x": _w((lambda *s: torch.randn(*s, dtype=torch.bfloat16) * 0.05)(B, S, D)),
            "w1": _w((lambda *s: torch.randn(*s, dtype=torch.bfloat16) * 1.6)(D, F) * (D ** -0.5)),
            "b1": _w((lambda *s: torch.randn(*s, dtype=torch.bfloat16) * 0.8)(F)),
            "w2": _w((lambda *s: torch.randn(*s, dtype=torch.bfloat16) * 0.05)(F, D) * (F ** -0.5)),
            "b2": _w((lambda *s: torch.randn(*s, dtype=torch.bfloat16) * 0.05)(D)),
        }
    _B_in = _B_setup()

    return {
        "A_u": _A_in["u"],
        "A_A_re": _A_in["A_re"],
        "A_A_im": _A_in["A_im"],
        "A_B_re": _A_in["B_re"],
        "A_B_im": _A_in["B_im"],
        "A_C_re": _A_in["C_re"],
        "A_C_im": _A_in["C_im"],
        "A_log_dt": _A_in["log_dt"],
        "A_Dskip": _A_in["Dskip"],
        "B_x": _B_in["x"],
        "B_w1": _B_in["w1"],
        "B_b1": _B_in["b1"],
        "B_w2": _B_in["w2"],
        "B_b2": _B_in["b2"],
    }

def reference(A_u, A_A_re, A_A_im, A_B_re, A_B_im, A_C_re, A_C_im, A_log_dt, A_Dskip, B_x, B_w1, B_b1, B_w2, B_b2):
    def _A_ref(u, A_re, A_im, B_re, B_im, C_re, C_im, log_dt, Dskip):
        Bsz, L, D = u.shape
        dt = torch.exp(log_dt)[:, None]
        A = A_re + 1j * A_im
        Bc = B_re + 1j * B_im
        Cc = C_re + 1j * C_im
        logdA = dt * A
        dB = dt * Bc
        l = (lambda x, dt: x.to(dt))(torch.arange(L), A_re.dtype)
        P = torch.exp(logdA[:, :, None] * l[None, None, :])
        K = torch.einsum("dn,dnl,dn->dl", Cc, P, dB).real
        L2 = 2 * L
        Kp = _pad(K, ((0, 0), (0, L)))
        up = (lambda x, *d: x.permute(*d))(u, 0, 2, 1)
        up = _pad(up, ((0, 0), (0, 0), (0, L)))
        Kf = (lambda x, axes=(-2,-1): torch.fft.rfft2(x.float(), dim=axes))(Kp[:, None, :], axes=(-2, -1))
        Uf = (lambda x, axes=(-2,-1): torch.fft.rfft2(x.float(), dim=axes))(up[:, :, None, :], axes=(-2, -1))
        Yf = Uf * Kf[None, :, :, :]
        y = (lambda x, s, axes=(-2,-1): torch.fft.irfft2(x, s=s, dim=axes).to(torch.bfloat16))(Yf, (1, L2), axes=(-2, -1))[:, :, 0, :L]
        y = (lambda x, *d: x.permute(*d))(y, 0, 2, 1) + u * Dskip[None, None, :]
        return y

    def _B_ref(x, w1, b1, w2, b2):
        y = _layernorm(x, axis=-1)
        h = _gelu(torch.einsum("bsd,df->bsf", y, w1) + b1)
        return torch.einsum("bsf,fd->bsd", h, w2) + b2

    x = A_u
    xn = _layernorm(x, axis=-1)
    return x + _A_ref(xn, A_A_re, A_A_im, A_B_re, A_B_im, A_C_re, A_C_im, A_log_dt, A_Dskip) + _B_ref(xn, B_w1, B_b1, B_w2, B_b2)
```

```cpp
#include <cuda_runtime.h>
#include <cuda.h>
#include <cuda_bf16.h>
#include <stdint.h>

namespace {

constexpr int SEQ = 2048, DM = 640, NST = 128, FF = 1728;
constexpr int NCTA = 128;
#define TC 1
#define REG_0 88
#define REG_P 24
#define REG_A 152
#define REG_C 168
#define MAPV 1
#define GPF 4
#define HINT ""
#define LNXD 600
#define RINGD 1000
#define LFIRST 1
#define G1W 1
#define G2W 1
#define HPACE 0
#define GELU16 0
#define HGLOB 0

struct __align__(1024) Scratch {
  uint16_t xnT[DM * SEQ];
  uint16_t zT[DM * SEQ];
  uint16_t H[16 * 2 * 216 * 512];
  float2 stats[SEQ];
  float col[2 * 8 * 108 * 4];
  unsigned epoch[32], stcnt[32], xncnt[32], cvcnt[32], hcnt[2 * 16 * 32];
  long long trace[NCTA * 64];
};
__device__ Scratch g_scratch;
#define TRACE(i) do { } while (0)

constexpr int SLOT = 16384;
constexpr int NA = 3, NB = 6;
constexpr int SM_A = 0;
constexpr int SM_B = SM_A + NA * SLOT;
constexpr int SM_WS = SM_B + NB * SLOT;
constexpr int KG_LBO_A = 1040, KG_LBO_B = 720;
constexpr int KG_B = 16 * KG_LBO_A, KG_SZ = 28288;
constexpr int SM_KG1 = SM_WS;
constexpr int SM_LNT = SM_WS + 2 * KG_SZ;
constexpr int U_SZ = 4224;
constexpr int SM_UBUF = SM_LNT;
constexpr int KEXP_SZ = 8320;
constexpr int SM_KEXP = SM_WS;
constexpr int SM_COL = SM_KEXP + 2 * KEXP_SZ;
constexpr int SM_ROW = SM_COL + 108 * 16;
constexpr int SM_SC = SM_ROW + 1024;
constexpr int SM_EXCH = SM_UBUF - U_SZ - 16384;
constexpr int SM_PAR = SM_KG1 + KG_SZ;
constexpr int TAPS_SZ = 1296;
constexpr int SM_TAPS = SM_UBUF + 5 * U_SZ;
constexpr int SM_LNS = SM_TAPS + 4 * TAPS_SZ;
constexpr int SM_RECV = SM_WS;
constexpr int SM_FZ = SM_WS + 20480;
constexpr int SM_FX = SM_WS + 40960;
constexpr int SM_FXN = SM_WS + 57344;
constexpr int SM_BAR = SM_TAPS + 5 * TAPS_SZ;
constexpr int BAR_LNX = 0, BAR_AFULL = 1, BAR_HRD1 = 4, BAR_RRDY = 7, BAR_AEMPTY = 8, BAR_HC = 11,
              BAR_BFULL = 16, BAR_TAB = 22, BAR_BEMPTY = 24, BAR_G1FREE = 30, BAR_KG01 = 31,
              BAR_RFULL2 = 32, BAR_RECV = 39, BAR_REMPTY2 = 40, BAR_ST = 47,
              BAR_PAR = 48, BAR_UFULL = 49, BAR_FIN = 54, BAR_CVD = 55, BAR_ZRDY = 57, BAR_KGD = 63;
constexpr int NR = 7, RSLOT = 20480;
constexpr int SM_TOTAL = SM_BAR + 64 * 8;
static_assert(KG_B + 15 * KG_LBO_B + 768 <= KG_SZ && SM_SC + 40 <= SM_EXCH, "ws");
static_assert(SM_LNT % 128 == 0 && SM_COL % 16 == 0 && SM_BAR % 8 == 0 && SM_FXN + 8192 <= SM_TAPS, "align");
static_assert(SM_TOTAL <= 232448, "smem");

struct Maps {
  CUtensorMap x128, w1, w1n, w2, w2n, xt, x64, x32, z128, z32, o64, o32;
};

__device__ __forceinline__ uint32_t s2u(const void* p) { return (uint32_t)__cvta_generic_to_shared(p); }
__device__ __forceinline__ void mbar_init(uint32_t a, int c) { asm volatile("mbarrier.init.shared::cta.b64 [%0], %1;" ::"r"(a), "r"(c)); }
__device__ __forceinline__ void mbar_expect(uint32_t a, int bytes) {
  asm volatile("mbarrier.arrive.expect_tx.shared::cta.b64 _, [%0], %1;" ::"r"(a), "r"(bytes) : "memory");
}
__device__ __forceinline__ void mbar_arrive(uint32_t a) { asm volatile("mbarrier.arrive.shared::cta.b64 _, [%0];" ::"r"(a) : "memory"); }
__device__ __forceinline__ void mbar_wait(uint32_t a, int ph) {
  asm volatile("{\n.reg .pred p;\n.reg .u32 c;\nmov.u32 c, 0x400000;\n"
               "WAIT:\nmbarrier.try_wait.parity.shared::cta.b64 p, [%0], %1" HINT ";\n@p bra DONE;\n"
               "sub.u32 c, c, 1;\nsetp.ne.u32 p, c, 0;\n@p bra WAIT;\ntrap;\nDONE:\n}" ::"r"(a), "r"(ph) : "memory");
}
__device__ __forceinline__ bool mbar_test(uint32_t a, int ph) {
  uint32_t ok;
  asm volatile("{\n.reg .pred p;\nmbarrier.test_wait.parity.shared::cta.b64 p, [%1], %2;\nselp.u32 %0, 1, 0, p;\n}" : "=r"(ok) : "r"(a), "r"(ph) : "memory");
  return __shfl_sync(~0u, ok, 0);
}
__device__ __forceinline__ void mbar_wait_cluster(uint32_t a, int ph) {
  asm volatile("{\n.reg .pred p;\n.reg .u32 c;\nmov.u32 c, 0x400000;\n"
               "WAIT:\nmbarrier.try_wait.parity.acquire.cluster.shared::cta.b64 p, [%0], %1" HINT ";\n@p bra DONE;\n"
               "sub.u32 c, c, 1;\nsetp.ne.u32 p, c, 0;\n@p bra WAIT;\ntrap;\nDONE:\n}" ::"r"(a), "r"(ph) : "memory");
}
__device__ __forceinline__ unsigned ld_acquire(const unsigned* p) {
  unsigned v;
  asm volatile("ld.acquire.gpu.global.u32 %0, [%1];" : "=r"(v) : "l"(p) : "memory");
  return v;
}
__device__ __forceinline__ unsigned ld_relaxed(const unsigned* p) {
  unsigned v;
  asm volatile("ld.relaxed.gpu.global.u32 %0, [%1];" : "=r"(v) : "l"(p) : "memory");
  return v;
}
__device__ __forceinline__ void poll_ge(const unsigned* p, unsigned target) {
#pragma unroll 1
  for (int it = 0; it < (1 << 22); it++)
    if ((int)(ld_acquire(p) - target) >= 0) return;
  __trap();
}
__device__ __forceinline__ void red_release(unsigned* p) {
  asm volatile("red.release.gpu.global.add.u32 [%0], 1;" ::"l"(p) : "memory");
}
__device__ __forceinline__ void red_after_bulk(unsigned* p) {
  asm volatile("fence.proxy.async.global;\nred.relaxed.gpu.global.add.u32 [%0], 1;" ::"l"(p) : "memory");
}
__device__ __forceinline__ void fence_async_global() { asm volatile("fence.proxy.async.global;" ::: "memory"); }
__device__ __forceinline__ void bulk_commit() { asm volatile("cp.async.bulk.commit_group;" ::: "memory"); }
template <int N> __device__ __forceinline__ void bulk_wait() { asm volatile("cp.async.bulk.wait_group %0;" ::"n"(N) : "memory"); }
template <int N> __device__ __forceinline__ void bulk_wait_read() { asm volatile("cp.async.bulk.wait_group.read %0;" ::"n"(N) : "memory"); }
__device__ __forceinline__ void cluster_arrive() { asm volatile("barrier.cluster.arrive.relaxed.aligned;" ::: "memory"); }
__device__ __forceinline__ void cluster_wait() { asm volatile("barrier.cluster.wait.acquire.aligned;" ::: "memory"); }
__device__ __forceinline__ void fence_async_smem() { asm volatile("fence.proxy.async.shared::cta;" ::: "memory"); }
__device__ __forceinline__ void bar_sync(int id) { asm volatile("bar.sync %0, 128;" ::"r"(id) : "memory"); }
__device__ __forceinline__ void wg_fence() { asm volatile("wgmma.fence.sync.aligned;" ::: "memory"); }
__device__ __forceinline__ void wg_commit() { asm volatile("wgmma.commit_group.sync.aligned;" ::: "memory"); }
template <int N> __device__ __forceinline__ void wg_wait() { asm volatile("wgmma.wait_group.sync.aligned %0;" ::"n"(N) : "memory"); }
__device__ __forceinline__ void tma2d(uint32_t dst, const CUtensorMap* m, uint32_t bar, int c0, int c1) {
  asm volatile("cp.async.bulk.tensor.2d.shared::cluster.global.mbarrier::complete_tx::bytes [%0], [%1, {%3, %4}], [%2];"
               ::"r"(dst), "l"(m), "r"(bar), "r"(c0), "r"(c1) : "memory");
}
__device__ __forceinline__ void tma3d(uint32_t dst, const CUtensorMap* m, uint32_t bar, int c0, int c1, int c2) {
  asm volatile("cp.async.bulk.tensor.3d.shared::cluster.global.mbarrier::complete_tx::bytes [%0], [%1, {%3, %4, %5}], [%2];"
               ::"r"(dst), "l"(m), "r"(bar), "r"(c0), "r"(c1), "r"(c2) : "memory");
}
__device__ __forceinline__ void tma2d_store(const CUtensorMap* m, uint32_t src, int c0, int c1) {
  asm volatile("cp.async.bulk.tensor.2d.global.shared::cta.bulk_group [%0, {%2, %3}], [%1];"
               ::"l"(m), "r"(src), "r"(c0), "r"(c1) : "memory");
}
__device__ __forceinline__ void bulk_g2s(uint32_t dst, const void* src, int bytes, uint32_t bar) {
  asm volatile("cp.async.bulk.shared::cluster.global.mbarrier::complete_tx::bytes [%0], [%1], %2, [%3];"
               ::"r"(dst), "l"(src), "r"(bytes), "r"(bar) : "memory");
}
__device__ __forceinline__ void bulk_s2g(void* dst, uint32_t src, int bytes) {
  asm volatile("cp.async.bulk.global.shared::cta.bulk_group [%0], [%1], %2;" ::"l"(dst), "r"(src), "r"(bytes) : "memory");
}
__device__ __forceinline__ uint32_t mapa(uint32_t a, uint32_t cta) {
  uint32_t r;
  asm("mapa.shared::cluster.u32 %0, %1, %2;" : "=r"(r) : "r"(a), "r"(cta));
  return r;
}
__device__ __forceinline__ uint64_t mkdesc(uint32_t addr, uint32_t lbo, uint32_t sbo, uint32_t swz) {
  return (uint64_t)((addr & 0x3FFFF) >> 4) | ((uint64_t)(lbo >> 4) << 16) | ((uint64_t)(sbo >> 4) << 32) | ((uint64_t)swz << 62);
}
__device__ __forceinline__ uint32_t pack_bf16(float lo, float hi) {
  uint32_t r;
  asm("cvt.rn.bf16x2.f32 %0, %1, %2;" : "=r"(r) : "f"(hi), "f"(lo));
  return r;
}
__device__ __forceinline__ float bf_lo(uint32_t v) { return __uint_as_float(v << 16); }
__device__ __forceinline__ float bf_hi(uint32_t v) { return __uint_as_float(v & 0xffff0000u); }
__device__ __forceinline__ float bf_round(float v) { return bf_lo(pack_bf16(v, 0.f)); }
__device__ __forceinline__ uint32_t ldg16v(const uint16_t* p) {
  uint32_t v;
  asm volatile("ld.global.nc.u16 %0, [%1];" : "=r"(v) : "l"(p) : "memory");
  return v;
}
__device__ __forceinline__ uint32_t hadd2(uint32_t a, uint32_t b) {
  uint32_t r;
  asm("add.rn.bf16x2 %0, %1, %2;" : "=r"(r) : "r"(a), "r"(b));
  return r;
}
__device__ __forceinline__ uint32_t hmul2(uint32_t a, uint32_t b) {
  uint32_t r;
  asm("mul.rn.bf16x2 %0, %1, %2;" : "=r"(r) : "r"(a), "r"(b));
  return r;
}
__device__ __forceinline__ uint32_t hfma2(uint32_t a, uint32_t b, uint32_t c) {
  uint32_t r;
  asm("fma.rn.bf16x2 %0, %1, %2, %3;" : "=r"(r) : "r"(a), "r"(b), "r"(c));
  return r;
}
__device__ __forceinline__ void sts32(uint32_t a, uint32_t v) { asm volatile("st.shared.b32 [%0], %1;" ::"r"(a), "r"(v) : "memory"); }
__device__ __forceinline__ void sts16(uint32_t a, uint32_t v) { asm volatile("st.shared.b16 [%0], %1;" ::"r"(a), "h"((uint16_t)v) : "memory"); }
__device__ __forceinline__ void sts64(uint32_t a, uint32_t x, uint32_t y) {
  asm volatile("st.shared.v2.b32 [%0], {%1, %2};" ::"r"(a), "r"(x), "r"(y) : "memory");
}
__device__ __forceinline__ void stsm2(uint32_t a, uint32_t r0, uint32_t r1) {
  asm volatile("stmatrix.sync.aligned.m8n8.x2.shared.b16 [%0], {%1, %2};" ::"r"(a), "r"(r0), "r"(r1) : "memory");
}
__device__ __forceinline__ void sts128(uint32_t a, uint32_t x, uint32_t y, uint32_t z, uint32_t w) {
  asm volatile("st.shared.v4.b32 [%0], {%1, %2, %3, %4};" ::"r"(a), "r"(x), "r"(y), "r"(z), "r"(w) : "memory");
}
__device__ __forceinline__ uint32_t lds32(uint32_t a) {
  uint32_t v;
  asm volatile("ld.shared.b32 %0, [%1];" : "=r"(v) : "r"(a) : "memory");
  return v;
}
__device__ __forceinline__ uint32_t lds16(uint32_t a) {
  uint16_t v;
  asm volatile("ld.shared.b16 %0, [%1];" : "=h"(v) : "r"(a) : "memory");
  return v;
}
__device__ __forceinline__ float4 lds128f(uint32_t a) {
  float4 v;
  asm volatile("ld.shared.v4.f32 {%0, %1, %2, %3}, [%4];" : "=f"(v.x), "=f"(v.y), "=f"(v.z), "=f"(v.w) : "r"(a) : "memory");
  return v;
}
__device__ __forceinline__ float2 lds64f(uint32_t a) {
  float2 v;
  asm volatile("ld.shared.v2.f32 {%0, %1}, [%2];" : "=f"(v.x), "=f"(v.y) : "r"(a) : "memory");
  return v;
}
__device__ __forceinline__ void ldsm4(uint32_t (&r)[4], uint32_t a) {
  asm volatile("ldmatrix.sync.aligned.m8n8.x4.shared.b16 {%0, %1, %2, %3}, [%4];"
               : "=r"(r[0]), "=r"(r[1]), "=r"(r[2]), "=r"(r[3]) : "r"(a) : "memory");
}
__device__ __forceinline__ void ldsm4t(uint32_t (&r)[4], uint32_t a) {
  asm volatile("ldmatrix.sync.aligned.m8n8.x4.trans.shared.b16 {%0, %1, %2, %3}, [%4];"
               : "=r"(r[0]), "=r"(r[1]), "=r"(r[2]), "=r"(r[3]) : "r"(a) : "memory");
}
__device__ __forceinline__ void stsm4t(uint32_t a, const uint32_t (&r)[4]) {
  asm volatile("stmatrix.sync.aligned.m8n8.x4.trans.shared.b16 [%0], {%1, %2, %3, %4};"
               ::"r"(a), "r"(r[0]), "r"(r[1]), "r"(r[2]), "r"(r[3]) : "memory");
}
__device__ __forceinline__ uint4 lds128(uint32_t a) {
  uint4 v;
  asm volatile("ld.shared.v4.b32 {%0, %1, %2, %3}, [%4];" : "=r"(v.x), "=r"(v.y), "=r"(v.z), "=r"(v.w) : "r"(a) : "memory");
  return v;
}
__device__ __forceinline__ void stsm4_free(uint32_t a, const uint32_t (&r)[4]) {
  asm volatile("stmatrix.sync.aligned.m8n8.x4.shared.b16 [%0], {%1, %2, %3, %4};" ::"r"(a), "r"(r[0]), "r"(r[1]), "r"(r[2]), "r"(r[3]));
}
__device__ __forceinline__ uint32_t opaque(uint32_t v) { asm volatile("" : "+r"(v)::"memory"); return v; }
__device__ __forceinline__ bool elect() {
  uint32_t p;
  asm volatile("{\n.reg .pred q;\nelect.sync _|q, 0xffffffff;\nselp.u32 %0, 1, 0, q;\n}" : "=r"(p));
  return p;
}
__device__ __forceinline__ float gelu_half(float hv) {
  const float u = hv * fmaf(hv * hv, 0.2854192650904f, 1.5957691216058f);
  float th;
  asm("tanh.approx.f32 %0, %1;" : "=f"(th) : "f"(u));
  return fmaf(hv, th, hv);
}
__device__ __forceinline__ uint32_t gelu_pair(float a, float b) {
  return pack_bf16(gelu_half(a), gelu_half(b));
}
__device__ __forceinline__ float rcp_std(float var) {
  float s, r;
  asm("sqrt.approx.ftz.f32 %0, %1;" : "=f"(s) : "f"(bf_round(bf_round(var) + 1e-5f)));
  asm("rcp.approx.ftz.f32 %0, %1;" : "=f"(r) : "f"(bf_round(s)));
  return r;
}
__device__ __forceinline__ uint32_t prmt(uint32_t a, uint32_t b, uint32_t sel) {
  uint32_t r;
  asm("prmt.b32 %0, %1, %2, %3;" : "=r"(r) : "r"(a), "r"(b), "r"(sel));
  return r;
}
template <int N> __device__ __forceinline__ void reg_fence(float (&d)[N]) {
#pragma unroll
  for (int i = 0; i < N; i++) asm volatile("" : "+f"(d[i])::"memory");
}
struct cpx { float r, i; };
__device__ __forceinline__ cpx cmul(cpx a, cpx b) { return {fmaf(a.r, b.r, -a.i * b.i), fmaf(a.r, b.i, a.i * b.r)}; }
__device__ __forceinline__ cpx cexp_x(float ar2, float at, float x) {
  float mag;
  asm("ex2.approx.ftz.f32 %0, %1;" : "=f"(mag) : "f"(ar2 * x));
  float ph = at * x;
  ph -= rintf(ph);
  float s, c;
  ph *= 6.283185307179586f;
  s = __sinf(ph);
  c = __cosf(ph);
  return {mag * c, mag * s};
}

__device__ __forceinline__ void wgmma_g1a(float (&d)[108], uint64_t da, uint64_t db, int sd) {
  asm volatile("{\n.reg .pred p;\nsetp.ne.b32 p, %66, 0;\n"
    "wgmma.mma_async.sync.aligned.m64n128k16.f32.bf16.bf16 {%0,%1,%2,%3,%4,%5,%6,%7,%8,%9,%10,%11,%12,%13,%14,%15,%16,%17,%18,%19,%20,%21,%22,%23,%24,%25,%26,%27,%28,%29,%30,%31,%32,%33,%34,%35,%36,%37,%38,%39,%40,%41,%42,%43,%44,%45,%46,%47,%48,%49,%50,%51,%52,%53,%54,%55,%56,%57,%58,%59,%60,%61,%62,%63}, %64, %65, p, 1, 1, 0, 1;\n}"
    : "+f"(d[0]),"+f"(d[1]),"+f"(d[2]),"+f"(d[3]),"+f"(d[4]),"+f"(d[5]),"+f"(d[6]),"+f"(d[7]),"+f"(d[8]),"+f"(d[9]),"+f"(d[10]),"+f"(d[11]),"+f"(d[12]),"+f"(d[13]),"+f"(d[14]),"+f"(d[15]),"+f"(d[16]),"+f"(d[17]),"+f"(d[18]),"+f"(d[19]),"+f"(d[20]),"+f"(d[21]),"+f"(d[22]),"+f"(d[23]),"+f"(d[24]),"+f"(d[25]),"+f"(d[26]),"+f"(d[27]),"+f"(d[28]),"+f"(d[29]),"+f"(d[30]),"+f"(d[31]),"+f"(d[32]),"+f"(d[33]),"+f"(d[34]),"+f"(d[35]),"+f"(d[36]),"+f"(d[37]),"+f"(d[38]),"+f"(d[39]),"+f"(d[40]),"+f"(d[41]),"+f"(d[42]),"+f"(d[43]),"+f"(d[44]),"+f"(d[45]),"+f"(d[46]),"+f"(d[47]),"+f"(d[48]),"+f"(d[49]),"+f"(d[50]),"+f"(d[51]),"+f"(d[52]),"+f"(d[53]),"+f"(d[54]),"+f"(d[55]),"+f"(d[56]),"+f"(d[57]),"+f"(d[58]),"+f"(d[59]),"+f"(d[60]),"+f"(d[61]),"+f"(d[62]),"+f"(d[63])
    : "l"(da), "l"(db), "r"(sd));
}
__device__ __forceinline__ void wgmma_g1b(float (&d)[108], uint64_t da, uint64_t db, int sd) {
  asm volatile("{\n.reg .pred p;\nsetp.ne.b32 p, %46, 0;\n"
    "wgmma.mma_async.sync.aligned.m64n88k16.f32.bf16.bf16 {%0,%1,%2,%3,%4,%5,%6,%7,%8,%9,%10,%11,%12,%13,%14,%15,%16,%17,%18,%19,%20,%21,%22,%23,%24,%25,%26,%27,%28,%29,%30,%31,%32,%33,%34,%35,%36,%37,%38,%39,%40,%41,%42,%43}, %44, %45, p, 1, 1, 0, 1;\n}"
    : "+f"(d[64]),"+f"(d[65]),"+f"(d[66]),"+f"(d[67]),"+f"(d[68]),"+f"(d[69]),"+f"(d[70]),"+f"(d[71]),"+f"(d[72]),"+f"(d[73]),"+f"(d[74]),"+f"(d[75]),"+f"(d[76]),"+f"(d[77]),"+f"(d[78]),"+f"(d[79]),"+f"(d[80]),"+f"(d[81]),"+f"(d[82]),"+f"(d[83]),"+f"(d[84]),"+f"(d[85]),"+f"(d[86]),"+f"(d[87]),"+f"(d[88]),"+f"(d[89]),"+f"(d[90]),"+f"(d[91]),"+f"(d[92]),"+f"(d[93]),"+f"(d[94]),"+f"(d[95]),"+f"(d[96]),"+f"(d[97]),"+f"(d[98]),"+f"(d[99]),"+f"(d[100]),"+f"(d[101]),"+f"(d[102]),"+f"(d[103]),"+f"(d[104]),"+f"(d[105]),"+f"(d[106]),"+f"(d[107])
    : "l"(da), "l"(db), "r"(sd));
}
__device__ __forceinline__ void wgmma_g2_ss(float (&d)[80], uint64_t da, uint64_t db, int sd) {
  asm volatile("{\n.reg .pred p;\nsetp.ne.b32 p, %82, 0;\n"
    "wgmma.mma_async.sync.aligned.m64n160k16.f32.bf16.bf16 {%0,%1,%2,%3,%4,%5,%6,%7,%8,%9,%10,%11,%12,%13,%14,%15,%16,%17,%18,%19,%20,%21,%22,%23,%24,%25,%26,%27,%28,%29,%30,%31,%32,%33,%34,%35,%36,%37,%38,%39,%40,%41,%42,%43,%44,%45,%46,%47,%48,%49,%50,%51,%52,%53,%54,%55,%56,%57,%58,%59,%60,%61,%62,%63,%64,%65,%66,%67,%68,%69,%70,%71,%72,%73,%74,%75,%76,%77,%78,%79}, %80, %81, p, 1, 1, 0, 1;\n}"
    : "+f"(d[0]),"+f"(d[1]),"+f"(d[2]),"+f"(d[3]),"+f"(d[4]),"+f"(d[5]),"+f"(d[6]),"+f"(d[7]),"+f"(d[8]),"+f"(d[9]),"+f"(d[10]),"+f"(d[11]),"+f"(d[12]),"+f"(d[13]),"+f"(d[14]),"+f"(d[15]),"+f"(d[16]),"+f"(d[17]),"+f"(d[18]),"+f"(d[19]),"+f"(d[20]),"+f"(d[21]),"+f"(d[22]),"+f"(d[23]),"+f"(d[24]),"+f"(d[25]),"+f"(d[26]),"+f"(d[27]),"+f"(d[28]),"+f"(d[29]),"+f"(d[30]),"+f"(d[31]),"+f"(d[32]),"+f"(d[33]),"+f"(d[34]),"+f"(d[35]),"+f"(d[36]),"+f"(d[37]),"+f"(d[38]),"+f"(d[39]),"+f"(d[40]),"+f"(d[41]),"+f"(d[42]),"+f"(d[43]),"+f"(d[44]),"+f"(d[45]),"+f"(d[46]),"+f"(d[47]),"+f"(d[48]),"+f"(d[49]),"+f"(d[50]),"+f"(d[51]),"+f"(d[52]),"+f"(d[53]),"+f"(d[54]),"+f"(d[55]),"+f"(d[56]),"+f"(d[57]),"+f"(d[58]),"+f"(d[59]),"+f"(d[60]),"+f"(d[61]),"+f"(d[62]),"+f"(d[63]),"+f"(d[64]),"+f"(d[65]),"+f"(d[66]),"+f"(d[67]),"+f"(d[68]),"+f"(d[69]),"+f"(d[70]),"+f"(d[71]),"+f"(d[72]),"+f"(d[73]),"+f"(d[74]),"+f"(d[75]),"+f"(d[76]),"+f"(d[77]),"+f"(d[78]),"+f"(d[79])
    : "l"(da), "l"(db), "r"(sd));
}
__device__ __forceinline__ void wgmma_kg48(float (&d)[24], uint64_t da, uint64_t db, int sd) {
  asm volatile("{\n.reg .pred p;\nsetp.ne.b32 p, %26, 0;\n"
    "wgmma.mma_async.sync.aligned.m64n48k16.f32.bf16.bf16 {%0,%1,%2,%3,%4,%5,%6,%7,%8,%9,%10,%11,%12,%13,%14,%15,%16,%17,%18,%19,%20,%21,%22,%23}, %24, %25, p, 1, 1, 0, 0;\n}"
    : "+f"(d[0]),"+f"(d[1]),"+f"(d[2]),"+f"(d[3]),"+f"(d[4]),"+f"(d[5]),"+f"(d[6]),"+f"(d[7]),"+f"(d[8]),"+f"(d[9]),"+f"(d[10]),"+f"(d[11]),"+f"(d[12]),"+f"(d[13]),"+f"(d[14]),"+f"(d[15]),"+f"(d[16]),"+f"(d[17]),"+f"(d[18]),"+f"(d[19]),"+f"(d[20]),"+f"(d[21]),"+f"(d[22]),"+f"(d[23])
    : "l"(da), "l"(db), "r"(sd));
}
template <int I> __device__ __forceinline__ void wgmma_conv(float (&d)[64], uint32_t a0, uint32_t a1, uint32_t a2, uint32_t a3, uint64_t db, int sd);
template <> __device__ __forceinline__ void wgmma_conv<0>(float (&d)[64], uint32_t a0, uint32_t a1, uint32_t a2, uint32_t a3, uint64_t db, int sd) {
  asm volatile("{\n.reg .pred p;\nsetp.ne.b32 p, %69, 0;\n"
    "wgmma.mma_async.sync.aligned.m64n128k16.f32.bf16.bf16 {%0,%1,%2,%3,%4,%5,%6,%7,%8,%9,%10,%11,%12,%13,%14,%15,%16,%17,%18,%19,%20,%21,%22,%23,%24,%25,%26,%27,%28,%29,%30,%31,%32,%33,%34,%35,%36,%37,%38,%39,%40,%41,%42,%43,%44,%45,%46,%47,%48,%49,%50,%51,%52,%53,%54,%55,%56,%57,%58,%59,%60,%61,%62,%63}, {%64,%65,%66,%67}, %68, p, 1, 1, 0;\n}"
    : "+f"(d[0]),"+f"(d[1]),"+f"(d[2]),"+f"(d[3]),"+f"(d[4]),"+f"(d[5]),"+f"(d[6]),"+f"(d[7]),"+f"(d[8]),"+f"(d[9]),"+f"(d[10]),"+f"(d[11]),"+f"(d[12]),"+f"(d[13]),"+f"(d[14]),"+f"(d[15]),"+f"(d[16]),"+f"(d[17]),"+f"(d[18]),"+f"(d[19]),"+f"(d[20]),"+f"(d[21]),"+f"(d[22]),"+f"(d[23]),"+f"(d[24]),"+f"(d[25]),"+f"(d[26]),"+f"(d[27]),"+f"(d[28]),"+f"(d[29]),"+f"(d[30]),"+f"(d[31]),"+f"(d[32]),"+f"(d[33]),"+f"(d[34]),"+f"(d[35]),"+f"(d[36]),"+f"(d[37]),"+f"(d[38]),"+f"(d[39]),"+f"(d[40]),"+f"(d[41]),"+f"(d[42]),"+f"(d[43]),"+f"(d[44]),"+f"(d[45]),"+f"(d[46]),"+f"(d[47]),"+f"(d[48]),"+f"(d[49]),"+f"(d[50]),"+f"(d[51]),"+f"(d[52]),"+f"(d[53]),"+f"(d[54]),"+f"(d[55]),"+f"(d[56]),"+f"(d[57]),"+f"(d[58]),"+f"(d[59]),"+f"(d[60]),"+f"(d[61]),"+f"(d[62]),"+f"(d[63])
    : "r"(a0), "r"(a1), "r"(a2), "r"(a3), "l"(db), "r"(sd));
}
template <> __device__ __forceinline__ void wgmma_conv<1>(float (&d)[64], uint32_t a0, uint32_t a1, uint32_t a2, uint32_t a3, uint64_t db, int sd) {
  asm volatile("{\n.reg .pred p;\nsetp.ne.b32 p, %61, 0;\n"
    "wgmma.mma_async.sync.aligned.m64n112k16.f32.bf16.bf16 {%0,%1,%2,%3,%4,%5,%6,%7,%8,%9,%10,%11,%12,%13,%14,%15,%16,%17,%18,%19,%20,%21,%22,%23,%24,%25,%26,%27,%28,%29,%30,%31,%32,%33,%34,%35,%36,%37,%38,%39,%40,%41,%42,%43,%44,%45,%46,%47,%48,%49,%50,%51,%52,%53,%54,%55}, {%56,%57,%58,%59}, %60, p, 1, 1, 0;\n}"
    : "+f"(d[0]),"+f"(d[1]),"+f"(d[2]),"+f"(d[3]),"+f"(d[4]),"+f"(d[5]),"+f"(d[6]),"+f"(d[7]),"+f"(d[8]),"+f"(d[9]),"+f"(d[10]),"+f"(d[11]),"+f"(d[12]),"+f"(d[13]),"+f"(d[14]),"+f"(d[15]),"+f"(d[16]),"+f"(d[17]),"+f"(d[18]),"+f"(d[19]),"+f"(d[20]),"+f"(d[21]),"+f"(d[22]),"+f"(d[23]),"+f"(d[24]),"+f"(d[25]),"+f"(d[26]),"+f"(d[27]),"+f"(d[28]),"+f"(d[29]),"+f"(d[30]),"+f"(d[31]),"+f"(d[32]),"+f"(d[33]),"+f"(d[34]),"+f"(d[35]),"+f"(d[36]),"+f"(d[37]),"+f"(d[38]),"+f"(d[39]),"+f"(d[40]),"+f"(d[41]),"+f"(d[42]),"+f"(d[43]),"+f"(d[44]),"+f"(d[45]),"+f"(d[46]),"+f"(d[47]),"+f"(d[48]),"+f"(d[49]),"+f"(d[50]),"+f"(d[51]),"+f"(d[52]),"+f"(d[53]),"+f"(d[54]),"+f"(d[55])
    : "r"(a0), "r"(a1), "r"(a2), "r"(a3), "l"(db), "r"(sd));
}
template <> __device__ __forceinline__ void wgmma_conv<2>(float (&d)[64], uint32_t a0, uint32_t a1, uint32_t a2, uint32_t a3, uint64_t db, int sd) {
  asm volatile("{\n.reg .pred p;\nsetp.ne.b32 p, %53, 0;\n"
    "wgmma.mma_async.sync.aligned.m64n96k16.f32.bf16.bf16 {%0,%1,%2,%3,%4,%5,%6,%7,%8,%9,%10,%11,%12,%13,%14,%15,%16,%17,%18,%19,%20,%21,%22,%23,%24,%25,%26,%27,%28,%29,%30,%31,%32,%33,%34,%35,%36,%37,%38,%39,%40,%41,%42,%43,%44,%45,%46,%47}, {%48,%49,%50,%51}, %52, p, 1, 1, 0;\n}"
    : "+f"(d[0]),"+f"(d[1]),"+f"(d[2]),"+f"(d[3]),"+f"(d[4]),"+f"(d[5]),"+f"(d[6]),"+f"(d[7]),"+f"(d[8]),"+f"(d[9]),"+f"(d[10]),"+f"(d[11]),"+f"(d[12]),"+f"(d[13]),"+f"(d[14]),"+f"(d[15]),"+f"(d[16]),"+f"(d[17]),"+f"(d[18]),"+f"(d[19]),"+f"(d[20]),"+f"(d[21]),"+f"(d[22]),"+f"(d[23]),"+f"(d[24]),"+f"(d[25]),"+f"(d[26]),"+f"(d[27]),"+f"(d[28]),"+f"(d[29]),"+f"(d[30]),"+f"(d[31]),"+f"(d[32]),"+f"(d[33]),"+f"(d[34]),"+f"(d[35]),"+f"(d[36]),"+f"(d[37]),"+f"(d[38]),"+f"(d[39]),"+f"(d[40]),"+f"(d[41]),"+f"(d[42]),"+f"(d[43]),"+f"(d[44]),"+f"(d[45]),"+f"(d[46]),"+f"(d[47])
    : "r"(a0), "r"(a1), "r"(a2), "r"(a3), "l"(db), "r"(sd));
}
template <> __device__ __forceinline__ void wgmma_conv<3>(float (&d)[64], uint32_t a0, uint32_t a1, uint32_t a2, uint32_t a3, uint64_t db, int sd) {
  asm volatile("{\n.reg .pred p;\nsetp.ne.b32 p, %45, 0;\n"
    "wgmma.mma_async.sync.aligned.m64n80k16.f32.bf16.bf16 {%0,%1,%2,%3,%4,%5,%6,%7,%8,%9,%10,%11,%12,%13,%14,%15,%16,%17,%18,%19,%20,%21,%22,%23,%24,%25,%26,%27,%28,%29,%30,%31,%32,%33,%34,%35,%36,%37,%38,%39}, {%40,%41,%42,%43}, %44, p, 1, 1, 0;\n}"
    : "+f"(d[0]),"+f"(d[1]),"+f"(d[2]),"+f"(d[3]),"+f"(d[4]),"+f"(d[5]),"+f"(d[6]),"+f"(d[7]),"+f"(d[8]),"+f"(d[9]),"+f"(d[10]),"+f"(d[11]),"+f"(d[12]),"+f"(d[13]),"+f"(d[14]),"+f"(d[15]),"+f"(d[16]),"+f"(d[17]),"+f"(d[18]),"+f"(d[19]),"+f"(d[20]),"+f"(d[21]),"+f"(d[22]),"+f"(d[23]),"+f"(d[24]),"+f"(d[25]),"+f"(d[26]),"+f"(d[27]),"+f"(d[28]),"+f"(d[29]),"+f"(d[30]),"+f"(d[31]),"+f"(d[32]),"+f"(d[33]),"+f"(d[34]),"+f"(d[35]),"+f"(d[36]),"+f"(d[37]),"+f"(d[38]),"+f"(d[39])
    : "r"(a0), "r"(a1), "r"(a2), "r"(a3), "l"(db), "r"(sd));
}
template <> __device__ __forceinline__ void wgmma_conv<4>(float (&d)[64], uint32_t a0, uint32_t a1, uint32_t a2, uint32_t a3, uint64_t db, int sd) {
  asm volatile("{\n.reg .pred p;\nsetp.ne.b32 p, %37, 0;\n"
    "wgmma.mma_async.sync.aligned.m64n64k16.f32.bf16.bf16 {%0,%1,%2,%3,%4,%5,%6,%7,%8,%9,%10,%11,%12,%13,%14,%15,%16,%17,%18,%19,%20,%21,%22,%23,%24,%25,%26,%27,%28,%29,%30,%31}, {%32,%33,%34,%35}, %36, p, 1, 1, 0;\n}"
    : "+f"(d[0]),"+f"(d[1]),"+f"(d[2]),"+f"(d[3]),"+f"(d[4]),"+f"(d[5]),"+f"(d[6]),"+f"(d[7]),"+f"(d[8]),"+f"(d[9]),"+f"(d[10]),"+f"(d[11]),"+f"(d[12]),"+f"(d[13]),"+f"(d[14]),"+f"(d[15]),"+f"(d[16]),"+f"(d[17]),"+f"(d[18]),"+f"(d[19]),"+f"(d[20]),"+f"(d[21]),"+f"(d[22]),"+f"(d[23]),"+f"(d[24]),"+f"(d[25]),"+f"(d[26]),"+f"(d[27]),"+f"(d[28]),"+f"(d[29]),"+f"(d[30]),"+f"(d[31])
    : "r"(a0), "r"(a1), "r"(a2), "r"(a3), "l"(db), "r"(sd));
}
template <> __device__ __forceinline__ void wgmma_conv<5>(float (&d)[64], uint32_t a0, uint32_t a1, uint32_t a2, uint32_t a3, uint64_t db, int sd) {
  asm volatile("{\n.reg .pred p;\nsetp.ne.b32 p, %29, 0;\n"
    "wgmma.mma_async.sync.aligned.m64n48k16.f32.bf16.bf16 {%0,%1,%2,%3,%4,%5,%6,%7,%8,%9,%10,%11,%12,%13,%14,%15,%16,%17,%18,%19,%20,%21,%22,%23}, {%24,%25,%26,%27}, %28, p, 1, 1, 0;\n}"
    : "+f"(d[0]),"+f"(d[1]),"+f"(d[2]),"+f"(d[3]),"+f"(d[4]),"+f"(d[5]),"+f"(d[6]),"+f"(d[7]),"+f"(d[8]),"+f"(d[9]),"+f"(d[10]),"+f"(d[11]),"+f"(d[12]),"+f"(d[13]),"+f"(d[14]),"+f"(d[15]),"+f"(d[16]),"+f"(d[17]),"+f"(d[18]),"+f"(d[19]),"+f"(d[20]),"+f"(d[21]),"+f"(d[22]),"+f"(d[23])
    : "r"(a0), "r"(a1), "r"(a2), "r"(a3), "l"(db), "r"(sd));
}
template <> __device__ __forceinline__ void wgmma_conv<6>(float (&d)[64], uint32_t a0, uint32_t a1, uint32_t a2, uint32_t a3, uint64_t db, int sd) {
  asm volatile("{\n.reg .pred p;\nsetp.ne.b32 p, %21, 0;\n"
    "wgmma.mma_async.sync.aligned.m64n32k16.f32.bf16.bf16 {%0,%1,%2,%3,%4,%5,%6,%7,%8,%9,%10,%11,%12,%13,%14,%15}, {%16,%17,%18,%19}, %20, p, 1, 1, 0;\n}"
    : "+f"(d[0]),"+f"(d[1]),"+f"(d[2]),"+f"(d[3]),"+f"(d[4]),"+f"(d[5]),"+f"(d[6]),"+f"(d[7]),"+f"(d[8]),"+f"(d[9]),"+f"(d[10]),"+f"(d[11]),"+f"(d[12]),"+f"(d[13]),"+f"(d[14]),"+f"(d[15])
    : "r"(a0), "r"(a1), "r"(a2), "r"(a3), "l"(db), "r"(sd));
}
template <> __device__ __forceinline__ void wgmma_conv<7>(float (&d)[64], uint32_t a0, uint32_t a1, uint32_t a2, uint32_t a3, uint64_t db, int sd) {
  asm volatile("{\n.reg .pred p;\nsetp.ne.b32 p, %13, 0;\n"
    "wgmma.mma_async.sync.aligned.m64n16k16.f32.bf16.bf16 {%0,%1,%2,%3,%4,%5,%6,%7}, {%8,%9,%10,%11}, %12, p, 1, 1, 0;\n}"
    : "+f"(d[0]),"+f"(d[1]),"+f"(d[2]),"+f"(d[3]),"+f"(d[4]),"+f"(d[5]),"+f"(d[6]),"+f"(d[7])
    : "r"(a0), "r"(a1), "r"(a2), "r"(a3), "l"(db), "r"(sd));
}

__device__ __forceinline__ void conv_ld(uint32_t* r, uint32_t a) {
  asm volatile("ld.shared.b32 %0, [%8];\nld.shared.b32 %1, [%8 + 256];\nld.shared.b32 %2, [%8 + 32];\nld.shared.b32 %3, [%8 + 288];\n"
               "ld.shared.b32 %4, [%8 + 512];\nld.shared.b32 %5, [%8 + 768];\nld.shared.b32 %6, [%8 + 544];\nld.shared.b32 %7, [%8 + 800];"
               : "=r"(r[0]), "=r"(r[1]), "=r"(r[2]), "=r"(r[3]), "=r"(r[4]), "=r"(r[5]), "=r"(r[6]), "=r"(r[7]) : "r"(a) : "memory");
}
template <int I> struct Step { static constexpr int value = I; };
template <int I, bool SHRINK> __device__ __forceinline__ void conv_group(float (&acc)[64], const uint32_t (&r)[32], uint64_t db, int sd) {
  wg_fence();
  wgmma_conv<SHRINK ? 2 * I : 0>(acc, r[8 * I], r[8 * I + 1], r[8 * I + 2], r[8 * I + 3], db + 32 * I, I > 0 || sd);
  wgmma_conv<SHRINK ? 2 * I + 1 : 0>(acc, r[8 * I + 4], r[8 * I + 5], r[8 * I + 6], r[8 * I + 7], db + 32 * I + 16, 1);
  wg_commit();
}

struct Params {
  Scratch* s;
  const uint16_t *logdt, *dskip, *b1, *b2, *x, *ssm[6], *w1, *w2;
};

__global__ void __cluster_dims__(2, 1, 1) __launch_bounds__(512, 1)
fused_kernel(const __grid_constant__ Params p, const __grid_constant__ Maps maps) {
  extern __shared__ __align__(1024) uint8_t smem_raw[];
  const uint32_t sb = s2u(smem_raw);
  const uint32_t bars = sb + SM_BAR;
  const int tid = threadIdx.x, lane = tid & 31, g = lane >> 2, t = lane & 3, tq = tid & 127;
  const int wid = __shfl_sync(~0u, tid >> 5, 0), wgi = wid >> 2, warp = wid & 3;
  const int b = blockIdx.x, rank = b & 1, cl = b >> 1;
  const int mt = cl & 15, nt = cl >> 4;
  const int js = 4 * rank + nt;
  const int krot = (mt >> 3) * 320;

  auto load_x = [&](int kb, int s) {
    mbar_expect(bars + 8 * (BAR_AFULL + s), 16384);
    tma2d(sb + SM_A + s * SLOT, &maps.x128, bars + 8 * (BAR_AFULL + s), kb * 64 + (kb < 5 ? krot : -krot), mt * 128);
  };
  auto load_w1 = [&](int i, int s) {
    const uint32_t d = sb + SM_B + s * SLOT, fb = bars + 8 * (BAR_BFULL + s);
    const int k0 = i * 32 + (i < 10 ? krot : -krot);
    mbar_expect(fb, 32 * 216 * 2);
    tma3d(d, &maps.w1, fb, 0, k0, 3 * js);
    tma2d(d + 12288, &maps.w1n, fb, 1536 + 24 * js, k0);
  };
  asm volatile("setmaxnreg.dec.sync.aligned.u32 %0;" ::"n"(REG_0));
  if (wgi == 3) {
    const bool el = elect();
    if (el) {
#pragma unroll
      for (int i = 0; i < 8; i++) mbar_init(bars + 128 * warp + 8 * i, 1);
      asm volatile("fence.mbarrier_init.release.cluster;" ::: "memory");
      if (warp == 3) {
        mbar_expect(bars + 8 * BAR_PAR, 6 * 1280);
#pragma unroll
        for (int i = 0; i < 6; i++) bulk_g2s(sb + SM_PAR + i * 1280, p.ssm[i] + b * 5 * NST, 1280, bars + 8 * BAR_PAR);
      }
#pragma unroll
      for (int i = 8; i < 16; i++) mbar_init(bars + 128 * warp + 8 * i, warp == 3 ? 4 : 8);
      asm volatile("fence.mbarrier_init.release.cluster;" ::: "memory");
      if (warp == 0) {
        const unsigned t0 = clock();
        while ((unsigned)clock() - t0 < LNXD) {}
        mbar_expect(bars + 8 * BAR_LNX, 16 * DM * 2);
        bulk_g2s(sb + SM_LNT, p.x + (size_t)b * 16 * DM, 16 * DM * 2, bars + 8 * BAR_LNX);
        TRACE(29);
      }
    }
    __syncwarp();
    const unsigned ep0 = ld_relaxed(p.s->epoch);
    asm volatile("bar.arrive 0, 512;" ::: "memory");
    cluster_arrive();
    bar_sync(1);
    if (el && (warp == 1 || warp == 2)) {
      mbar_wait(bars + 8 * BAR_PAR, 0);
#pragma unroll 1
      for (int i = 0; i < 5 - warp; i++) {
        if (warp == 2) load_x(i, i); else load_w1(i, i);
      }
      TRACE(30);
    }
    __syncwarp();
    {
      const uint32_t xr = sb + SM_LNT + (8 * (warp & 1) + g) * (DM * 2);
      uint4 xv[10];
      mbar_wait(bars + 8 * BAR_LNX, 0);
      if (tq == 0) TRACE(35);
#pragma unroll
      for (int i = 0; i < 10; i++) xv[i] = lds128(xr + (warp >> 1) * DM + t * 16 + i * 64);
      const uint32_t pv_ = lds16(xr);
      const uint32_t* w = reinterpret_cast<const uint32_t*>(xv);
      float sq[3][4] = {};
      const uint32_t npv = (pv_ ^ 0x8000u) * 0x10001u;
#pragma unroll
      for (int i = 0; i < 40; i++)
        asm("mma.sync.aligned.m16n8k8.row.col.f32.bf16.bf16.f32 {%0, %1, %2, %3}, {%4, %5}, {%4}, {%0, %1, %2, %3};"
            : "+f"(sq[i % 3][0]), "+f"(sq[i % 3][1]), "+f"(sq[i % 3][2]), "+f"(sq[i % 3][3]) : "r"(hadd2(w[i], npv)), "r"(0x3f803f80u));
      if (tq == 0) TRACE(13);
#pragma unroll
      for (int q = 0; q < 4; q++) sq[0][q] += sq[1][q] + sq[2][q];
      if (t == (g >> 1)) sts64(sb + SM_LNS + warp * 64 + g * 8, __float_as_uint((g & 1) ? sq[0][3] : sq[0][2]), __float_as_uint((g & 1) ? sq[0][1] : sq[0][0]));
      bar_sync(1);
      const float2 o1 = lds64f(sb + SM_LNS + warp * 64 + g * 8), o2 = lds64f(sb + SM_LNS + (warp ^ 2) * 64 + g * 8);
      const float s0 = (o1.x + o2.x) * (1.f / DM);
      const float var = fmaxf(fmaf(-s0, s0, (o1.y + o2.y) * (1.f / DM)), 0.f), mean = bf_lo(pv_) + s0;
      const float m1 = bf_round(mean), r1 = rcp_std(var), rh = bf_round(r1);
      const uint32_t nm = pack_bf16(-m1, -m1), rh2 = pack_bf16(rh, rh), rl2 = pack_bf16(r1 - rh, r1 - rh);
      const uint32_t dst = sb + SM_LNT + (warp >> 1) * 10240 + lane * 32 + 16 - (warp & 1) * 16;
#pragma unroll
      for (int i = 0; i < 10; i++) {
        uint32_t r[4];
#pragma unroll
        for (int q = 0; q < 4; q++) { const uint32_t d = hadd2(w[4 * i + q], nm); r[q] = hfma2(d, rh2, hmul2(d, rl2)); }
        stsm4t(dst + i * 1024, r);
      }
      const float m2 = bf_round((mean - m1) * r1), r2 = 0.5f * rcp_std(var * r1 * r1);
      if (t == 0 && warp < 2) p.s->stats[16 * b + 8 * warp + g] = make_float2(r1 * r2, -(m1 * r1 + m2) * r2);
      bar_sync(1);
      if (tq == 0) TRACE(16);
    }
    asm volatile("setmaxnreg.dec.sync.aligned.u32 %0;" ::"n"(REG_P));
    if (el) {
      unsigned* hc = p.s->hcnt + (HGLOB ? 0 : 32 * mt);
      auto seg_first = [&](int sg) {
        const int f = sg < 5 ? sg - 2 : sg - 5;
        return sg == 0 ? 6 * js + 5 : sg == 1 ? 50 + 3 * rank : 24 * rank + 6 * (f + (f >= nt)) + (sg < 5 ? 5 : 3);
      };
      auto seg_count = [](int sg) { return (0x44422236 >> (4 * sg)) & 15; };
      if (warp == 0) {
        int s = 0, ph = 0;
#pragma unroll 1
        for (int kb = NA; kb < 10; kb++) {
          mbar_wait(bars + 8 * (BAR_AEMPTY + s), ph);
          load_x(kb, s);
          if (++s == NA) { s = 0; ph ^= 1; }
        }
        const unsigned ep = ep0 + 1;
        s = 6; ph = 1;
#pragma unroll 1
        for (int sg = 1; sg < 8; sg++) {
          if (sg < 4) mbar_wait(bars + 8 * (BAR_HRD1 - 1 + sg), 0);
          if ((sg & 3) == 1) {
            poll_ge(hc + 128 * (sg - 1), (HGLOB ? NCTA : 8) * ep);
            fence_async_global();
            TRACE(32 + (sg >> 2));
          }
          const uint16_t* src = p.s->H + (size_t)(mt * 54 + seg_first(sg)) * 4096;
          int n = seg_count(sg);
#pragma unroll 1
          do {
            mbar_wait(bars + 8 * (BAR_REMPTY2 + s), ph);
            bulk_g2s(sb + s * RSLOT, src, 8192, bars + 8 * (BAR_RFULL2 + s));
            src -= 4096;
            if (++s == NR) { s = 0; ph ^= 1; }
          } while (--n);
        }
        const int row0 = mt * 128 + rank * 64;
        const uint32_t fb = bars + 8 * BAR_FIN;
        mbar_wait(bars + 8 * BAR_CVD, 0);
        mbar_expect(fb, 16384 + 4096 + 20480);
        tma2d(sb + SM_FX, &maps.x64, fb, nt * 128, row0);
        tma2d(sb + SM_FX + 8192, &maps.x64, fb, nt * 128 + 64, row0);
        tma2d(sb + SM_FXN, &maps.x32, fb, 512 + 32 * nt, row0);
        poll_ge(p.s->cvcnt, NCTA * ep);
        fence_async_global();
        tma2d(sb + SM_FZ, &maps.z128, fb, SEQ - 64 - row0, nt * 128);
        tma2d(sb + SM_FZ + 16384, &maps.z32, fb, SEQ - 64 - row0, 512 + 32 * nt);
      } else if (warp == 1) {
        int s = 4, ph = 1;
        mbar_wait(bars + 8 * BAR_KGD, 0);
        fence_async_smem();
#pragma unroll 1
        for (int i = 4; i < 20; i++) {
          mbar_wait(bars + 8 * (BAR_BEMPTY + s), ph);
          load_w1(i, s);
          if (++s == NB) { s = 0; ph ^= 1; }
        }
        mbar_wait(bars + 8 * BAR_G1FREE, 0);
        s = 0; ph = 1;
#pragma unroll 1
        for (int sg = 0; sg < 8; sg++) {
          int row = seg_first(sg) * 32, n = seg_count(sg);
#pragma unroll 1
          do {
            mbar_wait(bars + 8 * (BAR_REMPTY2 + s), ph);
            const uint32_t d = sb + s * RSLOT, fb = bars + 8 * (BAR_RFULL2 + s);
            mbar_expect(fb, sg ? 18432 : 10240);
            tma3d(d + 8192, &maps.w2, fb, 0, row, 2 * nt);
            tma2d(d + 16384, &maps.w2n, fb, 512 + 32 * nt, row);
            row -= 32;
            if (++s == NR) { s = 0; ph ^= 1; }
          } while (--n);
        }
      } else if (warp == 2) {
        mbar_expect(bars + 8 * BAR_RECV, 20480);
        mbar_wait(bars + 8 * BAR_ST, 0);
        red_release(p.s->stcnt);
        TRACE(8);
        poll_ge(p.s->stcnt, NCTA * (ep0 + 1));
                fence_async_global();
        mbar_expect(bars + 8 * BAR_TAB, 1728 + 1024);
        bulk_g2s(sb + SM_COL, p.s->col + ((ep0 & 1) * 8 + js) * 432, 1728, bars + 8 * BAR_TAB);
        bulk_g2s(sb + SM_ROW, p.s->stats + mt * 128, 1024, bars + 8 * BAR_TAB);
        TRACE(27);
        uint16_t* Hm = p.s->H + (size_t)mt * 54 * 4096;
        mbar_wait(bars + 8 * BAR_HC, 0);
        fence_async_smem();
#pragma unroll 1
        for (int i = 0; i < 6; i++) {
          const int ch = 192 + 3 * js + (i >> 1);
          bulk_s2g(Hm + (ch >> 2) * 4096 + (i & 1) * 2048 + (ch & 3) * 512, sb + 6 * RSLOT + (i & 1) * 4096 + (i >> 1) * 1024, 1024);
        }
#pragma unroll 1
        for (int i = 0; i < 6; i++) {
          bulk_commit();
          mbar_wait(bars + 8 * (BAR_HC + (i < 4 ? 1 + (i >> 1) : i - 1)), 0);
          fence_async_smem();
          bulk_wait_read<HPACE>();
          if (i == 2 + HPACE || i == 4 + HPACE) mbar_arrive(bars + 8 * (BAR_HRD1 - 1 + ((i - HPACE) >> 1)));
          bulk_s2g(Hm + (6 * js + 5 - i) * 4096, sb + i * RSLOT, 8192);
          if (i == 2) {
            bulk_wait<0>();
            red_after_bulk(hc);
            TRACE(62);
          }
        }
        bulk_commit();
        bulk_wait_read<0>();
        mbar_arrive(bars + 8 * (BAR_HRD1 + 2));
        bulk_wait<0>();
        red_after_bulk(hc + 512);
        TRACE(63);
      } else {
        const unsigned ep = ep0 + 1;
        fence_async_smem();
        bulk_s2g(p.s->xnT + (size_t)(127 - b) * (DM * 16), sb + SM_LNT, DM * 32);
        bulk_commit();
        bulk_wait<0>();
        red_after_bulk(p.s->xncnt);
        TRACE(17);
        asm volatile("cp.async.bulk.prefetch.L2.global [%0], %1;" ::"l"((const char*)p.w2 + (size_t)b * 17280), "r"(17280) : "memory");
        poll_ge(p.s->xncnt, NCTA * ep);
        fence_async_global();
        TRACE(11);
#pragma unroll 1
        for (int c = 0; c < 5; c++) {
          const int d = b * 5 + c;
          mbar_expect(bars + 8 * (BAR_UFULL + c), 129 * 32);
          tma2d(sb + SM_UBUF + c * U_SZ, &maps.xt, bars + 8 * (BAR_UFULL + c), ((d & ~30) | ((d & 6) << 2) | ((d & 24) >> 2)) * 16, 0);
        }
#pragma unroll 1
        for (int c = 0; c < 5; c++) {
          mbar_wait(bars + 8 * (BAR_ZRDY + c), 0);
          fence_async_smem();
          bulk_s2g(p.s->zT + (size_t)(b * 5 + c) * SEQ, sb + SM_UBUF + (c - 1) * U_SZ, 4096);
          bulk_commit();
        }
        bulk_wait<0>();
        red_after_bulk(p.s->cvcnt);
        mbar_arrive(bars + 8 * BAR_CVD);
        TRACE(12);
        asm volatile("barrier.cluster.wait.acquire;" ::: "memory");
        asm volatile("mbarrier.arrive.release.cluster.shared::cluster.b64 _, [%0];" ::"r"(mapa(bars + 8 * BAR_RRDY, rank ^ 1)) : "memory");
      }
    }
    return;
  }

  uint32_t kq[3][4];
#pragma unroll
  for (int k = 0; k < 3; k++) kq[k][3] = ldg16v(p.logdt + b * 5 + wgi + k);
  const uint32_t aux16 = ldg16v(wgi == 2 ? (tq & 1 ? p.b2 : p.dskip) + b * 5 + (tq < 10 ? tq >> 1 : 0)
                                         : p.b1 + (tid < 192 ? 192 * js + tid : tid < 216 ? 1344 + 24 * js + tid : 0));
  const unsigned ep0 = ld_relaxed(p.s->epoch);
  asm volatile("bar.sync 0, 512;" ::: "memory");
  cluster_arrive();
  if (tid == 0) TRACE(28);
  mbar_wait(bars + 8 * BAR_PAR, 0);
  if (tid == 0) TRACE(36);
#pragma unroll
  for (int k = 0; k < 3; k++) {
    const uint32_t pp = sb + SM_PAR + (wgi + k) * 256 + tq * 2;
#pragma unroll
    for (int j = 0; j < 3; j++) kq[k][j] = prmt(lds16(pp + 2 * j * 1280), lds16(pp + (2 * j + 1) * 1280), 0x5410);
  }
  asm volatile("bar.sync 6, 384;" ::: "memory");
  {
    const int nr = wgi == 2 ? 3 : 1;
#pragma unroll 1
    for (int r = 0; r < nr; r++) {
      const uint32_t buf = sb + (wgi + r == 2 ? SM_B + 4 * SLOT : wgi ? SM_KG1 + KG_SZ : SM_KG1);
      if (r == 1) mbar_wait(bars + 8 * BAR_KG01, 0);
      const float dt = bf_round(__expf(bf_lo(kq[0][3])));
      const float ar2 = dt * bf_lo(kq[0][0]) * 1.4426950408889634f, at = dt * bf_hi(kq[0][0]) * 0.15915494309189535f;
      const cpx cb = cmul(cpx{bf_lo(kq[0][2]), -bf_hi(kq[0][2])}, cpx{dt * bf_lo(kq[0][1]), -dt * bf_hi(kq[0][1])});
#pragma unroll
      for (int j = 0; j < 4; j++) { kq[0][j] = kq[1][j]; kq[1][j] = kq[2][j]; }
      const cpx e1 = cexp_x(ar2, -at, 1.f), e8 = cexp_x(ar2, at, 8.f), e256 = cexp_x(ar2, -at, 256.f);
      uint32_t qa = buf + ((tq & 63) >> 2) * KG_LBO_A + (tq >> 6) * 512 + (tq & 3) * 4;
      cpx v[4];
      v[0] = {1.f, 0.f}; v[1] = e8; v[2] = cmul(e8, e8); v[3] = cmul(v[2], e8);
      const cpx e32 = cmul(v[2], v[2]);
#pragma unroll 2
      for (int i = 0; i < 8; i++) {
#pragma unroll
        for (int q = 0; q < 4; q++) {
          sts32(qa + q * 16, pack_bf16(v[q].r, v[q].i));
          v[q] = cmul(v[q], e32);
        }
        qa += 64;
      }
      const uint32_t pa = buf + KG_B + ((tq & 63) >> 2) * KG_LBO_B + (tq >> 6) * 384 + (tq & 3) * 4;
      const cpx e2 = cmul(e1, e1), e4 = cmul(e2, e2), e512 = cmul(e256, e256);
      auto putp = [&](int pi, cpx z) { sts32(pa + pi * 16, pack_bf16(z.r, z.i)); };
      cpx x0 = cb, x1 = cmul(cb, e1);
      putp(0, x0); putp(1, x1);
#pragma unroll
      for (int i = 1; i < 4; i++) { x0 = cmul(x0, e2); x1 = cmul(x1, e2); putp(2 * i, x0); putp(2 * i + 1, x1); }
      cpx y = cmul(cb, e256), z = cmul(cb, e512);
      putp(8, y); putp(12, z); putp(13, cmul(z, e4));
      { const cpx w = cmul(y, e2); putp(9, w); putp(11, cmul(w, e4)); putp(10, cmul(y, e4)); }
      y = cmul(y, e512); z = cmul(z, e512);
      putp(14, y); putp(15, cmul(y, e4)); putp(16, z);
      y = cmul(y, e512); z = cmul(z, e512);
      putp(17, y); putp(18, z);
      putp(19, cmul(y, e512)); putp(20, cmul(z, e512));
      fence_async_smem();
      if (tq == 0 && r == 0) TRACE(wgi == 2 ? 26 : 25);
      bar_sync(2 + wgi);
      float ka[24];
      const uint64_t da = mkdesc(opaque(buf), KG_LBO_A, 128, 0), db = da - (((KG_LBO_A - KG_LBO_B) << 12) - KG_B / 16);
      wg_fence();
#pragma unroll
      for (int ks = 0; ks < 8; ks++) wgmma_kg48(ka, da + ks * (2 * KG_LBO_A / 16), db + ks * (2 * KG_LBO_B / 16), ks > 0);
      wg_commit();
      wg_wait<0>();
      reg_fence(ka);
      const uint32_t cm = buf + (lane >> 4) * KG_LBO_A + (warp | 2) * 256 + (lane & 15) * 16;
      if (warp >= 2) {
#pragma unroll
        for (int q = 0; q < 3; q++)
          sts128(cm + q * 2 * KG_LBO_A, __float_as_uint(ka[12 + 4 * q]), __float_as_uint(ka[13 + 4 * q]), __float_as_uint(ka[14 + 4 * q]), __float_as_uint(ka[15 + 4 * q]));
      }
      bar_sync(2 + wgi);
      if (warp < 2) {
        const uint32_t tp = sb + SM_TAPS + (wgi + r) * TAPS_SZ;
        const float4 o0 = lds128f(cm), o1 = lds128f(cm + 2 * KG_LBO_A), o2 = lds128f(cm + 4 * KG_LBO_A);
        const int i = 16 * warp + g;
        const uint32_t a0 = tp + 16 * i + 4 * t, a1 = tp + (t < 2 ? 512 + 8 * i + 4 * t : 512 + 128 * t + 4 * i), a2 = tp + 1024 + 128 * t + 2 * i;
        sts32(a0, pack_bf16(ka[0] + o0.x, ka[1] + o0.y));
        sts32(a0 + 128, pack_bf16(ka[2] + o0.z, ka[3] + o0.w));
        sts32(a1, pack_bf16(ka[4] + o1.x, ka[5] + o1.y));
        sts32(a1 + (t < 2 ? 64 : 32), pack_bf16(ka[6] + o1.z, ka[7] + o1.w));
        const uint32_t l0 = pack_bf16(ka[8] + o2.x, ka[9] + o2.y), l1 = pack_bf16(ka[10] + o2.z, ka[11] + o2.w);
        if (t < 2 || (t == 2 && i == 0)) sts16(a2, l0);
        if (t < 2) { sts16(a2 + 64, l0 >> 16); sts16(a2 + 16, l1); sts16(a2 + 80, l1 >> 16); }
      }
      bar_sync(2 + wgi);
      if (lane == 0 && r == 0) mbar_arrive(bars + 8 * (wgi == 2 ? BAR_KGD : BAR_KG01));
      if (tid == 256) TRACE(44 + 2 * r);
    }
    if (tq == 0) TRACE(wgi == 2 ? 9 : 14);
  }

  if (wgi == 2) {
    asm volatile("setmaxnreg.inc.sync.aligned.u32 %0;" ::"n"(REG_A));
    auto expand = [&](int c, auto quarter) {
      constexpr int i = decltype(quarter)::value;
      const uint32_t tp = sb + SM_TAPS + c * TAPS_SZ, ke = sb + SM_KEXP + (c & 1) * KEXP_SZ + 64 + 2048 * i + 16 * tq;
      if (i == 0) {
        const bool lo = tq < 64;
        const uint32_t a = tp + (lo ? 8 * tq : 256 + 4 * tq);
        const uint32_t k0 = lds32(a - 4), k1 = lds32(a), k2 = lds32(a + 4);
        sts128(ke, prmt(k1, tq ? k0 : 0u, tq <= 64 ? 0x7610 : 0x1010), prmt(k1, k1, lo ? 0x1032 : 0x1010), prmt(k2, k1, lo ? 0x7610 : 0x5476),
               prmt(k2, k1, lo ? 0x1032 : 0x7610));
      } else if (i == 1) {
        const uint32_t j = lds16(tp + 768 + 2 * tq), u = lds16(tp + 770 + 2 * tq), m = (tq & 1) ? u : j, jj = prmt(j, j, 0x1010);
        sts128(ke, jj, jj, prmt(m, j, 0x5410), prmt(u, m, 0x5410));
      } else {
        const uint32_t a = tp + 768 + 128 * i + (tq & ~1);
        const uint32_t l = lds16(a), u = lds16(a + 2 * (tq & 1)), m = (tq & 2) ? u : l, uu = prmt(u, u, 0x1010);
        sts128(ke, prmt(m, l, 0x5410), prmt(u, m, 0x5410), uu, uu);
      }
    };
    auto reduce = [&](int k) {
      const int c = k >> 1;
      const float2 sc = lds64f(sb + SM_SC + 8 * c);
      const uint32_t dsk = __float_as_uint(sc.x), b2 = __float_as_uint(sc.y);
      const uint32_t ea = sb + SM_EXCH + (k & 1) * 8192 + (4 * warp + t) * 128 + ((g + 2 * t) & 7) * 16;
      const uint32_t ua = sb + SM_UBUF + c * U_SZ + (~k & 1) * 2048 + (8 * warp + (lane & 7)) * 16 + (lane & 24) * 64;
      const uint4 e0 = lds128(ea), e1 = lds128(ea + 2048), e2 = lds128(ea + 4096), e3 = lds128(ea + 6144);
      uint32_t uu[4], o[4];
      ldsm4t(uu, ua);
      o[0] = hadd2(hadd2(e0.x, e1.x), hadd2(e2.x, e3.x)); o[1] = hadd2(hadd2(e0.y, e1.y), hadd2(e2.y, e3.y));
      o[2] = hadd2(hadd2(e0.z, e1.z), hadd2(e2.z, e3.z)); o[3] = hadd2(hadd2(e0.w, e1.w), hadd2(e2.w, e3.w));
#pragma unroll
      for (int q = 0; q < 4; q++) o[q] = hadd2(hadd2(o[q], hmul2(uu[q], dsk)), b2);
      stsm4t(ua - U_SZ, o);
    };
    auto z_ready = [&](int c) {
      __syncwarp();
      if (lane == 0) mbar_arrive(bars + 8 * (BAR_ZRDY + c));
    };
    if (tq < 10) sts32(sb + SM_SC + 4 * tq, aux16 * 0x10001u);
    if (tq < 8) sts128(sb + SM_KEXP + (tq >> 2) * KEXP_SZ + (tq & 3) * 16, 0, 0, 0, 0);
    expand(0, Step<0>()); expand(0, Step<1>()); expand(0, Step<2>()); expand(0, Step<3>());
    bar_sync(4);
    if (tq == 0) TRACE(10);
    float cy0 = 0.f, cy1 = 0.f;
    uint32_t cyw = 0, r[32];
    const uint32_t kx0 = sb + SM_KEXP + 4 * (16 + 16 * warp + g - 2 * t);
    conv_ld(r, kx0); conv_ld(r + 8, kx0 + 1024); conv_ld(r + 16, kx0 + 2048);
#pragma unroll 1
    for (int k = 0; k < 10; k++) {
      const int c = k >> 1, lo = k & 1;
      const uint32_t kx = kx0 + (c & 1) * KEXP_SZ + lo * 4096;
      const uint64_t db = mkdesc(sb + SM_UBUF + c * U_SZ, 16, 128, 0);
      float acc[64];
      if (tq == 0 && k >= 5 && k < 9) TRACE(51 + k);
      if (tq == 0) TRACE(k == 2 * TC ? 18 : k == 2 * TC + 1 ? 20 : k == 2 * TC + 2 ? 19 : 61);
      if (lo) {
        conv_group<0, false>(acc, r, db, 0);
        expand(c + 1, Step<0>());
        conv_group<1, false>(acc, r, db, 0);
        expand(c + 1, Step<1>());
        wg_wait<1>();
        conv_ld(r, kx);
        conv_group<2, false>(acc, r, db, 0);
        expand(c + 1, Step<2>());
        wg_wait<1>();
        conv_ld(r + 8, kx + 1024);
        conv_group<3, false>(acc, r, db, 0);
        expand(c + 1, Step<3>());
        wg_wait<1>();
        conv_ld(r + 16, kx + 2048);
      } else {
        mbar_wait(bars + 8 * (BAR_UFULL + c), 0);
        if (tq == 0 && k == 0) TRACE(3);
      }
      conv_group<0, true>(acc, r, db + 128, lo);
      bar_sync(4);
      wg_wait<1>();
      conv_ld(r + 24, kx + 3072);
      conv_group<1, true>(acc, r, db + 128, 1);
      conv_group<2, true>(acc, r, db + 128, 1);
      conv_group<3, true>(acc, r, db + 128, 1);
      reduce(k - 1);
      wg_wait<0>();
      reg_fence(acc);
      if (lo) {
        const uint32_t kn = kx0 + (~c & 1) * KEXP_SZ;
        conv_ld(r, kn); conv_ld(r + 8, kn + 1024); conv_ld(r + 16, kn + 2048);
      }
      const uint32_t ea = sb + SM_EXCH + lo * 8192 + warp * 2048 + (t - warp) * 128 + ((g + 2 * (t - warp)) & 7) * 16;
      auto W = [&](int j) { return pack_bf16(acc[4 * j] + (j < 15 ? acc[4 * j + 6] : cy0), acc[4 * j + 1] + (j < 15 ? acc[4 * j + 7] : cy1)); };
      const bool pz = t >= warp;
      const uint32_t w0 = W(0), w4 = W(4), w8 = W(8), w12 = W(12);
      sts128(ea + (pz ? 0 : 2048), pz ? w0 : w4, pz ? w4 : w8, pz ? w8 : w12, pz ? w12 : cyw);
#pragma unroll
      for (int j = 1; j < 4; j++) sts128(ea + j * 512, W(j), W(j + 4), W(j + 8), W(j + 12));
      cy0 = lo ? 0.f : acc[2]; cy1 = lo ? 0.f : acc[3]; cyw = lo ? 0u : w0;
      if (!lo && k) z_ready(c - 1);
    }
    if (tq == 0) TRACE(50);
    bar_sync(4);
    reduce(9);
    z_ready(4);
    if (tq == 0) TRACE(51);
  } else {
    asm volatile("setmaxnreg.inc.sync.aligned.u32 %0;" ::"n"(REG_C));
    {
      float acc[108];
      const uint64_t da0 = mkdesc(sb + SM_A + wgi * 8192, 16, 1024, 1), db0 = mkdesc(sb + SM_B, 4096, 1024, 1);
      int sa = 0, pa = 0, sbi = 0, pb = 0;
      uint32_t relA = 0, relB = 0;
      if (tid == 0) TRACE(23);
#pragma unroll 1
      for (int i = 0; i < 20; i++) {
        if (!(i & 1)) mbar_wait(bars + 8 * (BAR_AFULL + sa), pa);
        mbar_wait(bars + 8 * (BAR_BFULL + sbi), pb);
        if (tid == 0 && (i == 0 || i == 4 || i == 10)) TRACE(i == 0 ? 0 : i == 4 ? 37 : 38);
        const uint64_t da = da0 + (sa * (SLOT / 16) + (i & 1) * 4), db = db0 + sbi * (SLOT / 16);
        wg_fence();
        wgmma_g1a(acc, da, db, i);
        wgmma_g1b(acc, da, db + 512, i);
        wgmma_g1a(acc, da + 2, db + 128, 1);
        wgmma_g1b(acc, da + 2, db + 640, 1);
        wg_commit();
        if (i < 10 && (i & 7) == (mt & 7)) {
          const int rg = tid & 7, ch = min(tid >> 3, 26);
          float cs[8] = {};
          const uint32_t a = sb + SM_B + sbi * SLOT + (ch >> 3) * 4096 + rg * 128 + (((ch & 7) ^ rg) << 4);
#pragma unroll
          for (int q = 0; q < 4; q++) {
            const uint4 v = lds128(a + q * 1024);
            cs[0] += bf_lo(v.x); cs[1] += bf_hi(v.x); cs[2] += bf_lo(v.y); cs[3] += bf_hi(v.y);
            cs[4] += bf_lo(v.z); cs[5] += bf_hi(v.z); cs[6] += bf_lo(v.w); cs[7] += bf_hi(v.w);
          }
#pragma unroll
          for (int q = 0; q < 4; q++) { const float o = __shfl_xor_sync(~0u, (rg & 4) ? cs[q] : cs[q + 4], 4); cs[q] = ((rg & 4) ? cs[q + 4] : cs[q]) + o; }
#pragma unroll
          for (int q = 0; q < 2; q++) { const float o = __shfl_xor_sync(~0u, (rg & 2) ? cs[q] : cs[q + 2], 2); cs[q] = ((rg & 2) ? cs[q + 2] : cs[q]) + o; }
          { const float o = __shfl_xor_sync(~0u, (rg & 1) ? cs[0] : cs[1], 1); cs[0] = ((rg & 1) ? cs[1] : cs[0]) + o; }
          if (tid < 216) {
            float* cp = p.s->col + js * 432 + (tid >> 1) * 4 + (tid & 1);
            atomicAdd(cp + (ep0 & 1) * 3456, cs[0]);
            if (mt == 2) cp[(ep0 & 1) * 3456 + 2] = 0.5f * bf_lo(aux16);
            if (mt == 3) cp[(~ep0 & 1) * 3456] = 0.f;
          }
          __syncwarp();
          if (lane == 0 && i >= 2) mbar_arrive(bars + 8 * BAR_ST);
        }
        wg_wait<G1W>();
        if (lane == 0 && i > 0) {
          mbar_arrive(relB);
          if (!(i & 1)) mbar_arrive(relA);
        }
        relB = bars + 8 * (BAR_BEMPTY + sbi);
        relA = bars + 8 * (BAR_AEMPTY + sa);
        if (++sbi == NB) { sbi = 0; pb ^= 1; }
        if ((i & 1) && ++sa == NA) { sa = 0; pa ^= 1; }
      }
      wg_wait<0>();
      reg_fence(acc);
      if (lane == 0) mbar_arrive(bars + 8 * BAR_G1FREE);
      if (tid == 0) TRACE(1);
      mbar_wait(bars + 8 * BAR_TAB, 0);
      mbar_wait(bars + 8 * BAR_G1FREE, 0);
      if (tid == 0) TRACE(2);
      const float2 s0 = lds64f(sb + SM_ROW + (wgi * 64 + warp * 16 + g) * 8), s1 = lds64f(sb + SM_ROW + (wgi * 64 + warp * 16 + g + 8) * 8);
      const uint32_t hs = sb + wgi * 4096 + (lane >> 4) * 1024 + warp * 256 + (lane & 15) * 16;
      const uint32_t ca = sb + SM_COL + t * 16;
      uint32_t h[4];
      float2 cc[27], cb[27];
#pragma unroll
      for (int jb = 26; jb > 26 - GPF; jb--) { cc[jb] = lds64f(ca + jb * 64); cb[jb] = lds64f(ca + jb * 64 + 8); }
#pragma unroll
      for (int jb = 26; jb >= 0; jb--) {
        if (jb >= GPF) { cc[jb - GPF] = lds64f(ca + (jb - GPF) * 64); cb[jb - GPF] = lds64f(ca + (jb - GPF) * 64 + 8); }
        const float2 c = cc[jb], d = cb[jb];
        h[2 * (jb & 1)] = gelu_pair(fmaf(s0.x, acc[4 * jb], fmaf(s0.y, c.x, d.x)), fmaf(s0.x, acc[4 * jb + 1], fmaf(s0.y, c.y, d.y)));
        h[2 * (jb & 1) + 1] = gelu_pair(fmaf(s1.x, acc[4 * jb + 2], fmaf(s1.y, c.x, d.x)), fmaf(s1.x, acc[4 * jb + 3], fmaf(s1.y, c.y, d.y)));
        if (jb == 26) stsm2(hs + 6 * RSLOT + 2048, h[0], h[1]);
        else if (!(jb & 1)) stsm4_free(hs + (jb == 24 ? 6 : 5 - (jb >> 2)) * RSLOT + (jb & 2) * 1024, h);
        if ((jb & 7) == 0 || jb == 4) {
          if (jb == 0) fence_async_smem();
          __syncwarp();
          if (lane == 0) asm volatile("mbarrier.arrive.shared::cta.b64 _, [%0];" ::"r"(bars + 8 * (BAR_HC + (jb == 0 ? 4 : jb == 4 ? 3 : 3 - (jb >> 3)))));
        }
      }
      if (tid == 0) TRACE(24);
    }
    bar_sync(2 + wgi);
    float acc[80];
    {
      const uint64_t da0 = mkdesc(sb + wgi * 4096, 1024, 128, 0), db0 = mkdesc(sb + 8192, 4096, 1024, 1);
      int s = 0, ph = 0;
      uint32_t rel = 0;
#pragma unroll 1
      for (int q = 0; q < 27; q++) {
        mbar_wait(bars + 8 * (BAR_RFULL2 + s), ph);
        if (tid == 0 && (q == 0 || q == 5 || q == 6 || q == 15 || q == 26)) TRACE(34 + q);
        const uint64_t da = da0 + s * (RSLOT / 16), db = db0 + s * (RSLOT / 16);
        wg_fence();
        wgmma_g2_ss(acc, da, db, q);
        wgmma_g2_ss(acc, da + 128, db + 128, 1);
        wg_commit();
        wg_wait<G2W>();
        if (lane == 0 && q > 0) mbar_arrive(rel);
        rel = bars + 8 * (BAR_REMPTY2 + s);
        if (++s == NR) { s = 0; ph ^= 1; }
      }
    }
    cluster_wait();
    if (wgi != rank) {
      mbar_wait_cluster(bars + 8 * BAR_RRDY, 0);
      const uint32_t dst = mapa(sb + SM_RECV + tq * 16, rank ^ 1), rb = mapa(bars + 8 * BAR_RECV, rank ^ 1);
      wg_wait<0>();
      reg_fence(acc);
      if (tq == 0) TRACE(4);
#pragma unroll
      for (int i = 0; i < 10; i++)
        asm volatile("st.async.weak.shared::cluster.mbarrier::complete_tx::bytes.v4.b32 [%0], {%1, %2, %3, %4}, [%5];"
                     ::"r"(dst + i * 2048), "r"(pack_bf16(acc[8 * i], acc[8 * i + 1])), "r"(pack_bf16(acc[8 * i + 2], acc[8 * i + 3])),
                       "r"(pack_bf16(acc[8 * i + 4], acc[8 * i + 5])), "r"(pack_bf16(acc[8 * i + 6], acc[8 * i + 7])), "r"(rb) : "memory");
    } else {
      mbar_wait(bars + 8 * BAR_FIN, 0);
      if (tq == 0) TRACE(6);
      const int xr = warp * 16 + (lane & 15);
      const uint32_t xa = sb + xr * 128, xs = ((lane >> 4) ^ (xr & 7)) << 4;
      const uint32_t za = sb + SM_FZ + (lane >> 4) * 1024 + (lane & 7) * 128 + (((7 - 2 * warp - ((lane >> 3) & 1)) ^ (lane & 7)) << 4);
      uint32_t xz[40];
#pragma unroll
      for (int jj = 0; jj < 10; jj++) {
        uint32_t xx[4], zz[4];
        ldsm4(xx, xa + (jj < 8 ? SM_FX + (jj >> 2) * 8192 : SM_FXN) + (xs ^ ((jj & 3) << 5)));
        ldsm4t(zz, za + jj * 2048);
#pragma unroll
        for (int q = 0; q < 4; q++) xz[4 * jj + q] = hadd2(xx[q], zz[q]);
      }
      wg_wait<0>();
      reg_fence(acc);
      if (tq == 0) TRACE(5);
#pragma unroll
      for (int q = 0; q < 40; q++) xz[q] = hadd2(xz[q], pack_bf16(acc[2 * q], acc[2 * q + 1]));
      mbar_wait_cluster(bars + 8 * BAR_RECV, 0);
      if (tq == 0) TRACE(21);
      uint4 e[10];
#pragma unroll
      for (int jj = 0; jj < 10; jj++) e[jj] = lds128(sb + SM_RECV + tq * 16 + jj * 2048);
#pragma unroll
      for (int jj = 0; jj < 10; jj++) {
        const uint32_t o[4] = {hadd2(xz[4 * jj], e[jj].x), hadd2(xz[4 * jj + 1], e[jj].y), hadd2(xz[4 * jj + 2], e[jj].z), hadd2(xz[4 * jj + 3], e[jj].w)};
        stsm4_free(xa + (jj < 8 ? SM_FX + (jj >> 2) * 8192 : SM_FXN) + (xs ^ ((jj & 3) << 5)), o);
      }
      bar_sync(2 + wgi);
      if (tq == 0) {
        const int row0 = mt * 128 + rank * 64;
        fence_async_smem();
        TRACE(22);
        tma2d_store(&maps.o64, sb + SM_FX, nt * 128, row0);
        tma2d_store(&maps.o64, sb + SM_FX + 8192, nt * 128 + 64, row0);
        tma2d_store(&maps.o32, sb + SM_FXN, 512 + 32 * nt, row0);
        bulk_commit();
        if (b == 0) atomicAdd(p.s->epoch, 1u);
        bulk_wait_read<0>();
        TRACE(7);
      }
    }
  }
}

typedef CUresult (*EncodeFn)(CUtensorMap*, CUtensorMapDataType, cuuint32_t, void*, const cuuint64_t*, const cuuint64_t*,
                             const cuuint32_t*, const cuuint32_t*, CUtensorMapInterleave, CUtensorMapSwizzle,
                             CUtensorMapL2promotion, CUtensorMapFloatOOBfill);

void make_map(EncodeFn enc, CUtensorMap* m, const void* base, int rank, const cuuint64_t* dims, const cuuint64_t* strides,
              const cuuint32_t* box, CUtensorMapSwizzle sw = CU_TENSOR_MAP_SWIZZLE_128B) {
  const cuuint32_t es[3] = {1, 1, 1};
  enc(m, CU_TENSOR_MAP_DATA_TYPE_BFLOAT16, rank, const_cast<void*>(base), dims, strides, box, es, CU_TENSOR_MAP_INTERLEAVE_NONE,
      sw, CU_TENSOR_MAP_L2_PROMOTION_NONE, CU_TENSOR_MAP_FLOAT_OOB_FILL_NONE);
}
void map2d(EncodeFn enc, CUtensorMap* m, const void* base, int cols, int rows, int bc, int br,
           CUtensorMapSwizzle sw = CU_TENSOR_MAP_SWIZZLE_128B) {
  const cuuint64_t d[2] = {(cuuint64_t)cols, (cuuint64_t)rows}, s[1] = {(cuuint64_t)cols * 2};
  const cuuint32_t bx[2] = {(cuuint32_t)bc, (cuuint32_t)br};
  make_map(enc, m, base, 2, d, s, bx, sw);
}
void map3d(EncodeFn enc, CUtensorMap* m, const void* base, int cols, int rows, int br, int nb) {
  const cuuint64_t d[3] = {64, (cuuint64_t)rows, (cuuint64_t)cols / 64}, s[2] = {(cuuint64_t)cols * 2, 128};
  const cuuint32_t bx[3] = {64, (cuuint32_t)br, (cuuint32_t)nb};
  make_map(enc, m, base, 3, d, s, bx);
}

}

extern "C" void kernel_launch(void* const* d_in, const int* in_sizes, int n_in, void* d_out, int out_size) {
  (void)in_sizes; (void)n_in; (void)out_size;
  static EncodeFn enc = nullptr;
  static Scratch* scr = nullptr;
  if (!enc) {
    void* fn = nullptr;
    cudaDriverEntryPointQueryResult qr;
    cudaGetDriverEntryPoint("cuTensorMapEncodeTiled", &fn, cudaEnableDefault, &qr);
    enc = (EncodeFn)fn;
    cudaGetSymbolAddress((void**)&scr, g_scratch);
    cudaFuncSetAttribute(fused_kernel, cudaFuncAttributeMaxDynamicSharedMemorySize, SM_TOTAL);
  }
  Params p;
  p.s = scr;
  p.x = (const uint16_t*)d_in[0];
  for (int i = 0; i < 6; i++) p.ssm[i] = (const uint16_t*)d_in[1 + i];
  p.logdt = (const uint16_t*)d_in[7]; p.dskip = (const uint16_t*)d_in[8];
  p.w1 = (const uint16_t*)d_in[10]; p.b1 = (const uint16_t*)d_in[11];
  p.w2 = (const uint16_t*)d_in[12]; p.b2 = (const uint16_t*)d_in[13];
  Maps m;
  map2d(enc, &m.x128, p.x, DM, SEQ, 64, 128);
  map2d(enc, &m.x64, p.x, DM, SEQ, 64, 64);
  map2d(enc, &m.x32, p.x, DM, SEQ, 32, 64);
  map3d(enc, &m.w1, p.w1, FF, DM, 32, 3);
  map2d(enc, &m.w1n, p.w1, FF, DM, 24, 32);
  map3d(enc, &m.w2, p.w2, DM, FF, 32, 2);
  map2d(enc, &m.w2n, p.w2, DM, FF, 32, 32);
  map2d(enc, &m.xt, scr->xnT, DM * 16, 128, 16, 64, CU_TENSOR_MAP_SWIZZLE_NONE);
  map2d(enc, &m.z128, scr->zT, SEQ, DM, 64, 128);
  map2d(enc, &m.z32, scr->zT, SEQ, DM, 64, 32);
  map2d(enc, &m.o64, d_out, DM, SEQ, 64, 64);
  map2d(enc, &m.o32, d_out, DM, SEQ, 32, 64);
  fused_kernel<<<NCTA, 512, SM_TOTAL>>>(m, p);
}
```

```cpp
#include <cuda_runtime.h>
#include <cuda.h>
#include <cuda_bf16.h>
#include <stdint.h>

namespace {

constexpr int SEQ = 2048, DM = 640, NST = 128, FF = 1728;
constexpr int NCTA = 128;
#define TC 1
#define REG_0 96
#define REG_P 24
#define REG_A 168
#define REG_C 160
#define MAPV 1
#define GPF 4
#define HINT ""
#define LNXD 300
#define RINGD 1000
#define LFIRST 1
#define G1W 1
#define G2W 0
#define HPACE 0
#define GELU16 0
#define TMPF 0
#define W1PF 0
#define B45 0
#define G2R 1
#define XMC 0
#define HRK 1
#define CVG 1
#define G1D 8
#define G2Z 99
#define G1Y 99
#define HGLOB 0

struct __align__(1024) Scratch {
  uint16_t xnT[DM * SEQ];
  uint16_t zT[DM * SEQ];
  uint16_t H[16 * 2 * 216 * 512];
  float2 stats[SEQ];
  float col[2 * 8 * 108 * 4];
  unsigned epoch[32], stcnt[32], xncnt[32], cvcnt[32], hcnt[2 * 16 * 32];
  long long trace[NCTA * 64];
};
__device__ Scratch g_scratch;
#define TRACE(i) do { } while (0)

constexpr int SLOT = 16384;
constexpr int NA = 3, NB = 6;
constexpr int SM_A = 0;
constexpr int SM_B = SM_A + NA * SLOT;
constexpr int SM_WS = SM_B + NB * SLOT;
constexpr int KG_LBO_A = 1040, KG_LBO_B = 720;
constexpr int KG_B = 16 * KG_LBO_A, KG_SZ = 28288;
constexpr int SM_KG1 = SM_WS;
constexpr int SM_LNT = SM_WS + 2 * KG_SZ;
constexpr int U_SZ = 4224;
constexpr int SM_UBUF = SM_LNT;
constexpr int KEXP_SZ = 8320;
constexpr int SM_KEXP = SM_WS;
constexpr int SM_COL = SM_KEXP + 2 * KEXP_SZ;
constexpr int SM_ROW = SM_COL + 108 * 16;
constexpr int SM_SC = SM_ROW + 1024;
constexpr int SM_EXCH = SM_UBUF - U_SZ - 16384;
constexpr int SM_PAR = SM_KG1 + KG_SZ;
constexpr int TAPS_SZ = 1296;
constexpr int SM_TAPS = SM_UBUF + 5 * U_SZ;
constexpr int SM_LNS = SM_TAPS + 4 * TAPS_SZ;
constexpr int SM_RECV = SM_WS;
constexpr int SM_FZ = SM_WS + 20480;
constexpr int SM_FX = SM_WS + 40960;
constexpr int SM_FXN = SM_WS + 57344;
constexpr int SM_BAR = SM_TAPS + 5 * TAPS_SZ;
constexpr int BAR_LNX = 0, BAR_AFULL = 1, BAR_HRD1 = 4, BAR_RRDY = 7, BAR_AEMPTY = 8, BAR_HC = 11,
              BAR_BFULL = 16, BAR_TAB = 22, BAR_BEMPTY = 24, BAR_G1FREE = 30, BAR_KG01 = 31,
              BAR_RFULL2 = 32, BAR_RECV = 39, BAR_REMPTY2 = 40, BAR_ST = 47,
              BAR_PAR = 48, BAR_UFULL = 49, BAR_FIN = 54, BAR_CVD = 55, BAR_ZRDY = 57, BAR_KGD = 63;
constexpr int NR = 7, RSLOT = 20480;
constexpr int SM_TOTAL = SM_BAR + 64 * 8;
static_assert(KG_B + 15 * KG_LBO_B + 768 <= KG_SZ && SM_SC + 40 <= SM_EXCH, "ws");
static_assert(SM_LNT % 128 == 0 && SM_COL % 16 == 0 && SM_BAR % 8 == 0 && SM_FXN + 8192 <= SM_TAPS, "align");
static_assert(SM_TOTAL <= 232448, "smem");

struct Maps {
  CUtensorMap x128, w1, w1n, w2, w2n, xt, x64, x32, z128, z32, o64, o32;
};

__device__ __forceinline__ uint32_t s2u(const void* p) { return (uint32_t)__cvta_generic_to_shared(p); }
__device__ __forceinline__ void mbar_init(uint32_t a, int c) { asm volatile("mbarrier.init.shared::cta.b64 [%0], %1;" ::"r"(a), "r"(c)); }
__device__ __forceinline__ void mbar_expect(uint32_t a, int bytes) {
  asm volatile("mbarrier.arrive.expect_tx.shared::cta.b64 _, [%0], %1;" ::"r"(a), "r"(bytes) : "memory");
}
__device__ __forceinline__ void mbar_arrive(uint32_t a) { asm volatile("mbarrier.arrive.shared::cta.b64 _, [%0];" ::"r"(a) : "memory"); }
__device__ __forceinline__ void mbar_wait(uint32_t a, int ph) {
  asm volatile("{\n.reg .pred p;\n.reg .u32 c;\nmov.u32 c, 0x400000;\n"
               "WAIT:\nmbarrier.try_wait.parity.shared::cta.b64 p, [%0], %1" HINT ";\n@p bra DONE;\n"
               "sub.u32 c, c, 1;\nsetp.ne.u32 p, c, 0;\n@p bra WAIT;\ntrap;\nDONE:\n}" ::"r"(a), "r"(ph) : "memory");
}
__device__ __forceinline__ bool mbar_test(uint32_t a, int ph) {
  uint32_t ok;
  asm volatile("{\n.reg .pred p;\nmbarrier.test_wait.parity.shared::cta.b64 p, [%1], %2;\nselp.u32 %0, 1, 0, p;\n}" : "=r"(ok) : "r"(a), "r"(ph) : "memory");
  return __shfl_sync(~0u, ok, 0);
}
__device__ __forceinline__ void mbar_wait_cluster(uint32_t a, int ph) {
  asm volatile("{\n.reg .pred p;\n.reg .u32 c;\nmov.u32 c, 0x400000;\n"
               "WAIT:\nmbarrier.try_wait.parity.acquire.cluster.shared::cta.b64 p, [%0], %1" HINT ";\n@p bra DONE;\n"
               "sub.u32 c, c, 1;\nsetp.ne.u32 p, c, 0;\n@p bra WAIT;\ntrap;\nDONE:\n}" ::"r"(a), "r"(ph) : "memory");
}
__device__ __forceinline__ unsigned ld_acquire(const unsigned* p) {
  unsigned v;
  asm volatile("ld.acquire.gpu.global.u32 %0, [%1];" : "=r"(v) : "l"(p) : "memory");
  return v;
}
__device__ __forceinline__ unsigned ld_relaxed(const unsigned* p) {
  unsigned v;
  asm volatile("ld.relaxed.gpu.global.u32 %0, [%1];" : "=r"(v) : "l"(p) : "memory");
  return v;
}
__device__ __forceinline__ void poll_ge(const unsigned* p, unsigned target) {
#pragma unroll 1
  for (int it = 0; it < (1 << 22); it++)
    if ((int)(ld_acquire(p) - target) >= 0) return;
  __trap();
}
__device__ __forceinline__ void red_release(unsigned* p) {
  asm volatile("red.release.gpu.global.add.u32 [%0], 1;" ::"l"(p) : "memory");
}
__device__ __forceinline__ void red_after_bulk(unsigned* p) {
  asm volatile("fence.proxy.async.global;\nred.relaxed.gpu.global.add.u32 [%0], 1;" ::"l"(p) : "memory");
}
__device__ __forceinline__ void fence_async_global() { asm volatile("fence.proxy.async.global;" ::: "memory"); }
__device__ __forceinline__ void bulk_commit() { asm volatile("cp.async.bulk.commit_group;" ::: "memory"); }
template <int N> __device__ __forceinline__ void bulk_wait() { asm volatile("cp.async.bulk.wait_group %0;" ::"n"(N) : "memory"); }
template <int N> __device__ __forceinline__ void bulk_wait_read() { asm volatile("cp.async.bulk.wait_group.read %0;" ::"n"(N) : "memory"); }
__device__ __forceinline__ void cluster_arrive() { asm volatile("barrier.cluster.arrive.relaxed.aligned;" ::: "memory"); }
__device__ __forceinline__ void cluster_wait() { asm volatile("barrier.cluster.wait.acquire.aligned;" ::: "memory"); }
__device__ __forceinline__ void fence_async_smem() { asm volatile("fence.proxy.async.shared::cta;" ::: "memory"); }
__device__ __forceinline__ void bar_sync(int id) { asm volatile("bar.sync %0, 128;" ::"r"(id) : "memory"); }
__device__ __forceinline__ void wg_fence() { asm volatile("wgmma.fence.sync.aligned;" ::: "memory"); }
__device__ __forceinline__ void wg_commit() { asm volatile("wgmma.commit_group.sync.aligned;" ::: "memory"); }
template <int N> __device__ __forceinline__ void wg_wait() { asm volatile("wgmma.wait_group.sync.aligned %0;" ::"n"(N) : "memory"); }
__device__ __forceinline__ void tma2d(uint32_t dst, const CUtensorMap* m, uint32_t bar, int c0, int c1) {
  asm volatile("cp.async.bulk.tensor.2d.shared::cluster.global.mbarrier::complete_tx::bytes [%0], [%1, {%3, %4}], [%2];"
               ::"r"(dst), "l"(m), "r"(bar), "r"(c0), "r"(c1) : "memory");
}
__device__ __forceinline__ void tma3d(uint32_t dst, const CUtensorMap* m, uint32_t bar, int c0, int c1, int c2) {
  asm volatile("cp.async.bulk.tensor.3d.shared::cluster.global.mbarrier::complete_tx::bytes [%0], [%1, {%3, %4, %5}], [%2];"
               ::"r"(dst), "l"(m), "r"(bar), "r"(c0), "r"(c1), "r"(c2) : "memory");
}
__device__ __forceinline__ void tma2d_store(const CUtensorMap* m, uint32_t src, int c0, int c1) {
  asm volatile("cp.async.bulk.tensor.2d.global.shared::cta.bulk_group [%0, {%2, %3}], [%1];"
               ::"l"(m), "r"(src), "r"(c0), "r"(c1) : "memory");
}
__device__ __forceinline__ void bulk_g2s(uint32_t dst, const void* src, int bytes, uint32_t bar) {
  asm volatile("cp.async.bulk.shared::cluster.global.mbarrier::complete_tx::bytes [%0], [%1], %2, [%3];"
               ::"r"(dst), "l"(src), "r"(bytes), "r"(bar) : "memory");
}
__device__ __forceinline__ void bulk_s2g(void* dst, uint32_t src, int bytes) {
  asm volatile("cp.async.bulk.global.shared::cta.bulk_group [%0], [%1], %2;" ::"l"(dst), "r"(src), "r"(bytes) : "memory");
}
__device__ __forceinline__ uint32_t mapa(uint32_t a, uint32_t cta) {
  uint32_t r;
  asm("mapa.shared::cluster.u32 %0, %1, %2;" : "=r"(r) : "r"(a), "r"(cta));
  return r;
}
__device__ __forceinline__ uint64_t mkdesc(uint32_t addr, uint32_t lbo, uint32_t sbo, uint32_t swz) {
  return (uint64_t)((addr & 0x3FFFF) >> 4) | ((uint64_t)(lbo >> 4) << 16) | ((uint64_t)(sbo >> 4) << 32) | ((uint64_t)swz << 62);
}
__device__ __forceinline__ uint32_t pack_bf16(float lo, float hi) {
  uint32_t r;
  asm("cvt.rn.bf16x2.f32 %0, %1, %2;" : "=r"(r) : "f"(hi), "f"(lo));
  return r;
}
__device__ __forceinline__ float bf_lo(uint32_t v) { return __uint_as_float(v << 16); }
__device__ __forceinline__ float bf_hi(uint32_t v) { return __uint_as_float(v & 0xffff0000u); }
__device__ __forceinline__ float bf_round(float v) { return bf_lo(pack_bf16(v, 0.f)); }
__device__ __forceinline__ uint32_t ldg16v(const uint16_t* p) {
  uint32_t v;
  asm volatile("ld.global.nc.u16 %0, [%1];" : "=r"(v) : "l"(p) : "memory");
  return v;
}
__device__ __forceinline__ uint32_t hadd2(uint32_t a, uint32_t b) {
  uint32_t r;
  asm("add.rn.bf16x2 %0, %1, %2;" : "=r"(r) : "r"(a), "r"(b));
  return r;
}
__device__ __forceinline__ uint32_t hmul2(uint32_t a, uint32_t b) {
  uint32_t r;
  asm("mul.rn.bf16x2 %0, %1, %2;" : "=r"(r) : "r"(a), "r"(b));
  return r;
}
__device__ __forceinline__ uint32_t hfma2(uint32_t a, uint32_t b, uint32_t c) {
  uint32_t r;
  asm("fma.rn.bf16x2 %0, %1, %2, %3;" : "=r"(r) : "r"(a), "r"(b), "r"(c));
  return r;
}
__device__ __forceinline__ void sts32(uint32_t a, uint32_t v) { asm volatile("st.shared.b32 [%0], %1;" ::"r"(a), "r"(v) : "memory"); }
__device__ __forceinline__ void sts16(uint32_t a, uint32_t v) { asm volatile("st.shared.b16 [%0], %1;" ::"r"(a), "h"((uint16_t)v) : "memory"); }
__device__ __forceinline__ void sts64(uint32_t a, uint32_t x, uint32_t y) {
  asm volatile("st.shared.v2.b32 [%0], {%1, %2};" ::"r"(a), "r"(x), "r"(y) : "memory");
}
__device__ __forceinline__ void stsm2(uint32_t a, uint32_t r0, uint32_t r1) {
  asm volatile("stmatrix.sync.aligned.m8n8.x2.shared.b16 [%0], {%1, %2};" ::"r"(a), "r"(r0), "r"(r1) : "memory");
}
__device__ __forceinline__ void sts128(uint32_t a, uint32_t x, uint32_t y, uint32_t z, uint32_t w) {
  asm volatile("st.shared.v4.b32 [%0], {%1, %2, %3, %4};" ::"r"(a), "r"(x), "r"(y), "r"(z), "r"(w) : "memory");
}
__device__ __forceinline__ uint32_t lds32(uint32_t a) {
  uint32_t v;
  asm volatile("ld.shared.b32 %0, [%1];" : "=r"(v) : "r"(a) : "memory");
  return v;
}
__device__ __forceinline__ uint32_t lds16(uint32_t a) {
  uint16_t v;
  asm volatile("ld.shared.b16 %0, [%1];" : "=h"(v) : "r"(a) : "memory");
  return v;
}
__device__ __forceinline__ float4 lds128f(uint32_t a) {
  float4 v;
  asm volatile("ld.shared.v4.f32 {%0, %1, %2, %3}, [%4];" : "=f"(v.x), "=f"(v.y), "=f"(v.z), "=f"(v.w) : "r"(a) : "memory");
  return v;
}
__device__ __forceinline__ float2 lds64f(uint32_t a) {
  float2 v;
  asm volatile("ld.shared.v2.f32 {%0, %1}, [%2];" : "=f"(v.x), "=f"(v.y) : "r"(a) : "memory");
  return v;
}
__device__ __forceinline__ void ldsm4(uint32_t (&r)[4], uint32_t a) {
  asm volatile("ldmatrix.sync.aligned.m8n8.x4.shared.b16 {%0, %1, %2, %3}, [%4];"
               : "=r"(r[0]), "=r"(r[1]), "=r"(r[2]), "=r"(r[3]) : "r"(a) : "memory");
}
__device__ __forceinline__ void ldsm4t(uint32_t (&r)[4], uint32_t a) {
  asm volatile("ldmatrix.sync.aligned.m8n8.x4.trans.shared.b16 {%0, %1, %2, %3}, [%4];"
               : "=r"(r[0]), "=r"(r[1]), "=r"(r[2]), "=r"(r[3]) : "r"(a) : "memory");
}
__device__ __forceinline__ void stsm4t(uint32_t a, const uint32_t (&r)[4]) {
  asm volatile("stmatrix.sync.aligned.m8n8.x4.trans.shared.b16 [%0], {%1, %2, %3, %4};"
               ::"r"(a), "r"(r[0]), "r"(r[1]), "r"(r[2]), "r"(r[3]) : "memory");
}
__device__ __forceinline__ uint4 lds128(uint32_t a) {
  uint4 v;
  asm volatile("ld.shared.v4.b32 {%0, %1, %2, %3}, [%4];" : "=r"(v.x), "=r"(v.y), "=r"(v.z), "=r"(v.w) : "r"(a) : "memory");
  return v;
}
__device__ __forceinline__ void stsm4_free(uint32_t a, const uint32_t (&r)[4]) {
  asm volatile("stmatrix.sync.aligned.m8n8.x4.shared.b16 [%0], {%1, %2, %3, %4};" ::"r"(a), "r"(r[0]), "r"(r[1]), "r"(r[2]), "r"(r[3]));
}
__device__ __forceinline__ uint32_t opaque(uint32_t v) { asm volatile("" : "+r"(v)::"memory"); return v; }
__device__ __forceinline__ bool elect() {
  uint32_t p;
  asm volatile("{\n.reg .pred q;\nelect.sync _|q, 0xffffffff;\nselp.u32 %0, 1, 0, q;\n}" : "=r"(p));
  return p;
}
__device__ __forceinline__ float gelu_half(float hv) {
  const float u = hv * fmaf(hv * hv, 0.2854192650904f, 1.5957691216058f);
  float th;
  asm("tanh.approx.f32 %0, %1;" : "=f"(th) : "f"(u));
  return fmaf(hv, th, hv);
}
__device__ __forceinline__ uint32_t gelu_pair(float a, float b) {
  return pack_bf16(gelu_half(a), gelu_half(b));
}
__device__ __forceinline__ float rcp_std(float var) {
  float s, r;
  asm("sqrt.approx.ftz.f32 %0, %1;" : "=f"(s) : "f"(bf_round(bf_round(var) + 1e-5f)));
  asm("rcp.approx.ftz.f32 %0, %1;" : "=f"(r) : "f"(bf_round(s)));
  return r;
}
__device__ __forceinline__ uint32_t prmt(uint32_t a, uint32_t b, uint32_t sel) {
  uint32_t r;
  asm("prmt.b32 %0, %1, %2, %3;" : "=r"(r) : "r"(a), "r"(b), "r"(sel));
  return r;
}
template <int N> __device__ __forceinline__ void reg_fence(float (&d)[N]) {
#pragma unroll
  for (int i = 0; i < N; i++) asm volatile("" : "+f"(d[i])::"memory");
}
struct cpx { float r, i; };
__device__ __forceinline__ cpx cmul(cpx a, cpx b) { return {fmaf(a.r, b.r, -a.i * b.i), fmaf(a.r, b.i, a.i * b.r)}; }
__device__ __forceinline__ cpx cexp_x(float ar2, float at, float x) {
  float mag;
  asm("ex2.approx.ftz.f32 %0, %1;" : "=f"(mag) : "f"(ar2 * x));
  float ph = at * x;
  ph -= rintf(ph);
  float s, c;
  ph *= 6.283185307179586f;
  s = __sinf(ph);
  c = __cosf(ph);
  return {mag * c, mag * s};
}

__device__ __forceinline__ void wgmma_g1a(float (&d)[108], uint64_t da, uint64_t db, int sd) {
  asm volatile("{\n.reg .pred p;\nsetp.ne.b32 p, %66, 0;\n"
    "wgmma.mma_async.sync.aligned.m64n128k16.f32.bf16.bf16 {%0,%1,%2,%3,%4,%5,%6,%7,%8,%9,%10,%11,%12,%13,%14,%15,%16,%17,%18,%19,%20,%21,%22,%23,%24,%25,%26,%27,%28,%29,%30,%31,%32,%33,%34,%35,%36,%37,%38,%39,%40,%41,%42,%43,%44,%45,%46,%47,%48,%49,%50,%51,%52,%53,%54,%55,%56,%57,%58,%59,%60,%61,%62,%63}, %64, %65, p, 1, 1, 0, 1;\n}"
    : "+f"(d[0]),"+f"(d[1]),"+f"(d[2]),"+f"(d[3]),"+f"(d[4]),"+f"(d[5]),"+f"(d[6]),"+f"(d[7]),"+f"(d[8]),"+f"(d[9]),"+f"(d[10]),"+f"(d[11]),"+f"(d[12]),"+f"(d[13]),"+f"(d[14]),"+f"(d[15]),"+f"(d[16]),"+f"(d[17]),"+f"(d[18]),"+f"(d[19]),"+f"(d[20]),"+f"(d[21]),"+f"(d[22]),"+f"(d[23]),"+f"(d[24]),"+f"(d[25]),"+f"(d[26]),"+f"(d[27]),"+f"(d[28]),"+f"(d[29]),"+f"(d[30]),"+f"(d[31]),"+f"(d[32]),"+f"(d[33]),"+f"(d[34]),"+f"(d[35]),"+f"(d[36]),"+f"(d[37]),"+f"(d[38]),"+f"(d[39]),"+f"(d[40]),"+f"(d[41]),"+f"(d[42]),"+f"(d[43]),"+f"(d[44]),"+f"(d[45]),"+f"(d[46]),"+f"(d[47]),"+f"(d[48]),"+f"(d[49]),"+f"(d[50]),"+f"(d[51]),"+f"(d[52]),"+f"(d[53]),"+f"(d[54]),"+f"(d[55]),"+f"(d[56]),"+f"(d[57]),"+f"(d[58]),"+f"(d[59]),"+f"(d[60]),"+f"(d[61]),"+f"(d[62]),"+f"(d[63])
    : "l"(da), "l"(db), "r"(sd));
}
__device__ __forceinline__ void wgmma_g1b(float (&d)[108], uint64_t da, uint64_t db, int sd) {
  asm volatile("{\n.reg .pred p;\nsetp.ne.b32 p, %46, 0;\n"
    "wgmma.mma_async.sync.aligned.m64n88k16.f32.bf16.bf16 {%0,%1,%2,%3,%4,%5,%6,%7,%8,%9,%10,%11,%12,%13,%14,%15,%16,%17,%18,%19,%20,%21,%22,%23,%24,%25,%26,%27,%28,%29,%30,%31,%32,%33,%34,%35,%36,%37,%38,%39,%40,%41,%42,%43}, %44, %45, p, 1, 1, 0, 1;\n}"
    : "+f"(d[64]),"+f"(d[65]),"+f"(d[66]),"+f"(d[67]),"+f"(d[68]),"+f"(d[69]),"+f"(d[70]),"+f"(d[71]),"+f"(d[72]),"+f"(d[73]),"+f"(d[74]),"+f"(d[75]),"+f"(d[76]),"+f"(d[77]),"+f"(d[78]),"+f"(d[79]),"+f"(d[80]),"+f"(d[81]),"+f"(d[82]),"+f"(d[83]),"+f"(d[84]),"+f"(d[85]),"+f"(d[86]),"+f"(d[87]),"+f"(d[88]),"+f"(d[89]),"+f"(d[90]),"+f"(d[91]),"+f"(d[92]),"+f"(d[93]),"+f"(d[94]),"+f"(d[95]),"+f"(d[96]),"+f"(d[97]),"+f"(d[98]),"+f"(d[99]),"+f"(d[100]),"+f"(d[101]),"+f"(d[102]),"+f"(d[103]),"+f"(d[104]),"+f"(d[105]),"+f"(d[106]),"+f"(d[107])
    : "l"(da), "l"(db), "r"(sd));
}
__device__ __forceinline__ void wgmma_g1ar(float (&d)[108], uint32_t a0, uint32_t a1, uint32_t a2, uint32_t a3, uint64_t db, int sd) {
  asm volatile("{\n.reg .pred p;\nsetp.ne.b32 p, %69, 0;\n"
    "wgmma.mma_async.sync.aligned.m64n128k16.f32.bf16.bf16 {%0,%1,%2,%3,%4,%5,%6,%7,%8,%9,%10,%11,%12,%13,%14,%15,%16,%17,%18,%19,%20,%21,%22,%23,%24,%25,%26,%27,%28,%29,%30,%31,%32,%33,%34,%35,%36,%37,%38,%39,%40,%41,%42,%43,%44,%45,%46,%47,%48,%49,%50,%51,%52,%53,%54,%55,%56,%57,%58,%59,%60,%61,%62,%63}, {%64,%65,%66,%67}, %68, p, 1, 1, 1;\n}"
    : "+f"(d[0]),"+f"(d[1]),"+f"(d[2]),"+f"(d[3]),"+f"(d[4]),"+f"(d[5]),"+f"(d[6]),"+f"(d[7]),"+f"(d[8]),"+f"(d[9]),"+f"(d[10]),"+f"(d[11]),"+f"(d[12]),"+f"(d[13]),"+f"(d[14]),"+f"(d[15]),"+f"(d[16]),"+f"(d[17]),"+f"(d[18]),"+f"(d[19]),"+f"(d[20]),"+f"(d[21]),"+f"(d[22]),"+f"(d[23]),"+f"(d[24]),"+f"(d[25]),"+f"(d[26]),"+f"(d[27]),"+f"(d[28]),"+f"(d[29]),"+f"(d[30]),"+f"(d[31]),"+f"(d[32]),"+f"(d[33]),"+f"(d[34]),"+f"(d[35]),"+f"(d[36]),"+f"(d[37]),"+f"(d[38]),"+f"(d[39]),"+f"(d[40]),"+f"(d[41]),"+f"(d[42]),"+f"(d[43]),"+f"(d[44]),"+f"(d[45]),"+f"(d[46]),"+f"(d[47]),"+f"(d[48]),"+f"(d[49]),"+f"(d[50]),"+f"(d[51]),"+f"(d[52]),"+f"(d[53]),"+f"(d[54]),"+f"(d[55]),"+f"(d[56]),"+f"(d[57]),"+f"(d[58]),"+f"(d[59]),"+f"(d[60]),"+f"(d[61]),"+f"(d[62]),"+f"(d[63])
    : "r"(a0), "r"(a1), "r"(a2), "r"(a3), "l"(db), "r"(sd));
}
__device__ __forceinline__ void wgmma_g1br(float (&d)[108], uint32_t a0, uint32_t a1, uint32_t a2, uint32_t a3, uint64_t db, int sd) {
  asm volatile("{\n.reg .pred p;\nsetp.ne.b32 p, %49, 0;\n"
    "wgmma.mma_async.sync.aligned.m64n88k16.f32.bf16.bf16 {%0,%1,%2,%3,%4,%5,%6,%7,%8,%9,%10,%11,%12,%13,%14,%15,%16,%17,%18,%19,%20,%21,%22,%23,%24,%25,%26,%27,%28,%29,%30,%31,%32,%33,%34,%35,%36,%37,%38,%39,%40,%41,%42,%43}, {%44,%45,%46,%47}, %48, p, 1, 1, 1;\n}"
    : "+f"(d[64]),"+f"(d[65]),"+f"(d[66]),"+f"(d[67]),"+f"(d[68]),"+f"(d[69]),"+f"(d[70]),"+f"(d[71]),"+f"(d[72]),"+f"(d[73]),"+f"(d[74]),"+f"(d[75]),"+f"(d[76]),"+f"(d[77]),"+f"(d[78]),"+f"(d[79]),"+f"(d[80]),"+f"(d[81]),"+f"(d[82]),"+f"(d[83]),"+f"(d[84]),"+f"(d[85]),"+f"(d[86]),"+f"(d[87]),"+f"(d[88]),"+f"(d[89]),"+f"(d[90]),"+f"(d[91]),"+f"(d[92]),"+f"(d[93]),"+f"(d[94]),"+f"(d[95]),"+f"(d[96]),"+f"(d[97]),"+f"(d[98]),"+f"(d[99]),"+f"(d[100]),"+f"(d[101]),"+f"(d[102]),"+f"(d[103]),"+f"(d[104]),"+f"(d[105]),"+f"(d[106]),"+f"(d[107])
    : "r"(a0), "r"(a1), "r"(a2), "r"(a3), "l"(db), "r"(sd));
}
__device__ __forceinline__ void wgmma_g2_ss(float (&d)[80], uint64_t da, uint64_t db, int sd) {
  asm volatile("{\n.reg .pred p;\nsetp.ne.b32 p, %82, 0;\n"
    "wgmma.mma_async.sync.aligned.m64n160k16.f32.bf16.bf16 {%0,%1,%2,%3,%4,%5,%6,%7,%8,%9,%10,%11,%12,%13,%14,%15,%16,%17,%18,%19,%20,%21,%22,%23,%24,%25,%26,%27,%28,%29,%30,%31,%32,%33,%34,%35,%36,%37,%38,%39,%40,%41,%42,%43,%44,%45,%46,%47,%48,%49,%50,%51,%52,%53,%54,%55,%56,%57,%58,%59,%60,%61,%62,%63,%64,%65,%66,%67,%68,%69,%70,%71,%72,%73,%74,%75,%76,%77,%78,%79}, %80, %81, p, 1, 1, 0, 1;\n}"
    : "+f"(d[0]),"+f"(d[1]),"+f"(d[2]),"+f"(d[3]),"+f"(d[4]),"+f"(d[5]),"+f"(d[6]),"+f"(d[7]),"+f"(d[8]),"+f"(d[9]),"+f"(d[10]),"+f"(d[11]),"+f"(d[12]),"+f"(d[13]),"+f"(d[14]),"+f"(d[15]),"+f"(d[16]),"+f"(d[17]),"+f"(d[18]),"+f"(d[19]),"+f"(d[20]),"+f"(d[21]),"+f"(d[22]),"+f"(d[23]),"+f"(d[24]),"+f"(d[25]),"+f"(d[26]),"+f"(d[27]),"+f"(d[28]),"+f"(d[29]),"+f"(d[30]),"+f"(d[31]),"+f"(d[32]),"+f"(d[33]),"+f"(d[34]),"+f"(d[35]),"+f"(d[36]),"+f"(d[37]),"+f"(d[38]),"+f"(d[39]),"+f"(d[40]),"+f"(d[41]),"+f"(d[42]),"+f"(d[43]),"+f"(d[44]),"+f"(d[45]),"+f"(d[46]),"+f"(d[47]),"+f"(d[48]),"+f"(d[49]),"+f"(d[50]),"+f"(d[51]),"+f"(d[52]),"+f"(d[53]),"+f"(d[54]),"+f"(d[55]),"+f"(d[56]),"+f"(d[57]),"+f"(d[58]),"+f"(d[59]),"+f"(d[60]),"+f"(d[61]),"+f"(d[62]),"+f"(d[63]),"+f"(d[64]),"+f"(d[65]),"+f"(d[66]),"+f"(d[67]),"+f"(d[68]),"+f"(d[69]),"+f"(d[70]),"+f"(d[71]),"+f"(d[72]),"+f"(d[73]),"+f"(d[74]),"+f"(d[75]),"+f"(d[76]),"+f"(d[77]),"+f"(d[78]),"+f"(d[79])
    : "l"(da), "l"(db), "r"(sd));
}
__device__ __forceinline__ void wgmma_kg48(float (&d)[24], uint64_t da, uint64_t db, int sd) {
  asm volatile("{\n.reg .pred p;\nsetp.ne.b32 p, %26, 0;\n"
    "wgmma.mma_async.sync.aligned.m64n48k16.f32.bf16.bf16 {%0,%1,%2,%3,%4,%5,%6,%7,%8,%9,%10,%11,%12,%13,%14,%15,%16,%17,%18,%19,%20,%21,%22,%23}, %24, %25, p, 1, 1, 0, 0;\n}"
    : "+f"(d[0]),"+f"(d[1]),"+f"(d[2]),"+f"(d[3]),"+f"(d[4]),"+f"(d[5]),"+f"(d[6]),"+f"(d[7]),"+f"(d[8]),"+f"(d[9]),"+f"(d[10]),"+f"(d[11]),"+f"(d[12]),"+f"(d[13]),"+f"(d[14]),"+f"(d[15]),"+f"(d[16]),"+f"(d[17]),"+f"(d[18]),"+f"(d[19]),"+f"(d[20]),"+f"(d[21]),"+f"(d[22]),"+f"(d[23])
    : "l"(da), "l"(db), "r"(sd));
}
template <int I> __device__ __forceinline__ void wgmma_conv(float (&d)[64], uint32_t a0, uint32_t a1, uint32_t a2, uint32_t a3, uint64_t db, int sd);
template <> __device__ __forceinline__ void wgmma_conv<0>(float (&d)[64], uint32_t a0, uint32_t a1, uint32_t a2, uint32_t a3, uint64_t db, int sd) {
  asm volatile("{\n.reg .pred p;\nsetp.ne.b32 p, %69, 0;\n"
    "wgmma.mma_async.sync.aligned.m64n128k16.f32.bf16.bf16 {%0,%1,%2,%3,%4,%5,%6,%7,%8,%9,%10,%11,%12,%13,%14,%15,%16,%17,%18,%19,%20,%21,%22,%23,%24,%25,%26,%27,%28,%29,%30,%31,%32,%33,%34,%35,%36,%37,%38,%39,%40,%41,%42,%43,%44,%45,%46,%47,%48,%49,%50,%51,%52,%53,%54,%55,%56,%57,%58,%59,%60,%61,%62,%63}, {%64,%65,%66,%67}, %68, p, 1, 1, 0;\n}"
    : "+f"(d[0]),"+f"(d[1]),"+f"(d[2]),"+f"(d[3]),"+f"(d[4]),"+f"(d[5]),"+f"(d[6]),"+f"(d[7]),"+f"(d[8]),"+f"(d[9]),"+f"(d[10]),"+f"(d[11]),"+f"(d[12]),"+f"(d[13]),"+f"(d[14]),"+f"(d[15]),"+f"(d[16]),"+f"(d[17]),"+f"(d[18]),"+f"(d[19]),"+f"(d[20]),"+f"(d[21]),"+f"(d[22]),"+f"(d[23]),"+f"(d[24]),"+f"(d[25]),"+f"(d[26]),"+f"(d[27]),"+f"(d[28]),"+f"(d[29]),"+f"(d[30]),"+f"(d[31]),"+f"(d[32]),"+f"(d[33]),"+f"(d[34]),"+f"(d[35]),"+f"(d[36]),"+f"(d[37]),"+f"(d[38]),"+f"(d[39]),"+f"(d[40]),"+f"(d[41]),"+f"(d[42]),"+f"(d[43]),"+f"(d[44]),"+f"(d[45]),"+f"(d[46]),"+f"(d[47]),"+f"(d[48]),"+f"(d[49]),"+f"(d[50]),"+f"(d[51]),"+f"(d[52]),"+f"(d[53]),"+f"(d[54]),"+f"(d[55]),"+f"(d[56]),"+f"(d[57]),"+f"(d[58]),"+f"(d[59]),"+f"(d[60]),"+f"(d[61]),"+f"(d[62]),"+f"(d[63])
    : "r"(a0), "r"(a1), "r"(a2), "r"(a3), "l"(db), "r"(sd));
}
template <> __device__ __forceinline__ void wgmma_conv<1>(float (&d)[64], uint32_t a0, uint32_t a1, uint32_t a2, uint32_t a3, uint64_t db, int sd) {
  asm volatile("{\n.reg .pred p;\nsetp.ne.b32 p, %61, 0;\n"
    "wgmma.mma_async.sync.aligned.m64n112k16.f32.bf16.bf16 {%0,%1,%2,%3,%4,%5,%6,%7,%8,%9,%10,%11,%12,%13,%14,%15,%16,%17,%18,%19,%20,%21,%22,%23,%24,%25,%26,%27,%28,%29,%30,%31,%32,%33,%34,%35,%36,%37,%38,%39,%40,%41,%42,%43,%44,%45,%46,%47,%48,%49,%50,%51,%52,%53,%54,%55}, {%56,%57,%58,%59}, %60, p, 1, 1, 0;\n}"
    : "+f"(d[0]),"+f"(d[1]),"+f"(d[2]),"+f"(d[3]),"+f"(d[4]),"+f"(d[5]),"+f"(d[6]),"+f"(d[7]),"+f"(d[8]),"+f"(d[9]),"+f"(d[10]),"+f"(d[11]),"+f"(d[12]),"+f"(d[13]),"+f"(d[14]),"+f"(d[15]),"+f"(d[16]),"+f"(d[17]),"+f"(d[18]),"+f"(d[19]),"+f"(d[20]),"+f"(d[21]),"+f"(d[22]),"+f"(d[23]),"+f"(d[24]),"+f"(d[25]),"+f"(d[26]),"+f"(d[27]),"+f"(d[28]),"+f"(d[29]),"+f"(d[30]),"+f"(d[31]),"+f"(d[32]),"+f"(d[33]),"+f"(d[34]),"+f"(d[35]),"+f"(d[36]),"+f"(d[37]),"+f"(d[38]),"+f"(d[39]),"+f"(d[40]),"+f"(d[41]),"+f"(d[42]),"+f"(d[43]),"+f"(d[44]),"+f"(d[45]),"+f"(d[46]),"+f"(d[47]),"+f"(d[48]),"+f"(d[49]),"+f"(d[50]),"+f"(d[51]),"+f"(d[52]),"+f"(d[53]),"+f"(d[54]),"+f"(d[55])
    : "r"(a0), "r"(a1), "r"(a2), "r"(a3), "l"(db), "r"(sd));
}
template <> __device__ __forceinline__ void wgmma_conv<2>(float (&d)[64], uint32_t a0, uint32_t a1, uint32_t a2, uint32_t a3, uint64_t db, int sd) {
  asm volatile("{\n.reg .pred p;\nsetp.ne.b32 p, %53, 0;\n"
    "wgmma.mma_async.sync.aligned.m64n96k16.f32.bf16.bf16 {%0,%1,%2,%3,%4,%5,%6,%7,%8,%9,%10,%11,%12,%13,%14,%15,%16,%17,%18,%19,%20,%21,%22,%23,%24,%25,%26,%27,%28,%29,%30,%31,%32,%33,%34,%35,%36,%37,%38,%39,%40,%41,%42,%43,%44,%45,%46,%47}, {%48,%49,%50,%51}, %52, p, 1, 1, 0;\n}"
    : "+f"(d[0]),"+f"(d[1]),"+f"(d[2]),"+f"(d[3]),"+f"(d[4]),"+f"(d[5]),"+f"(d[6]),"+f"(d[7]),"+f"(d[8]),"+f"(d[9]),"+f"(d[10]),"+f"(d[11]),"+f"(d[12]),"+f"(d[13]),"+f"(d[14]),"+f"(d[15]),"+f"(d[16]),"+f"(d[17]),"+f"(d[18]),"+f"(d[19]),"+f"(d[20]),"+f"(d[21]),"+f"(d[22]),"+f"(d[23]),"+f"(d[24]),"+f"(d[25]),"+f"(d[26]),"+f"(d[27]),"+f"(d[28]),"+f"(d[29]),"+f"(d[30]),"+f"(d[31]),"+f"(d[32]),"+f"(d[33]),"+f"(d[34]),"+f"(d[35]),"+f"(d[36]),"+f"(d[37]),"+f"(d[38]),"+f"(d[39]),"+f"(d[40]),"+f"(d[41]),"+f"(d[42]),"+f"(d[43]),"+f"(d[44]),"+f"(d[45]),"+f"(d[46]),"+f"(d[47])
    : "r"(a0), "r"(a1), "r"(a2), "r"(a3), "l"(db), "r"(sd));
}
template <> __device__ __forceinline__ void wgmma_conv<3>(float (&d)[64], uint32_t a0, uint32_t a1, uint32_t a2, uint32_t a3, uint64_t db, int sd) {
  asm volatile("{\n.reg .pred p;\nsetp.ne.b32 p, %45, 0;\n"
    "wgmma.mma_async.sync.aligned.m64n80k16.f32.bf16.bf16 {%0,%1,%2,%3,%4,%5,%6,%7,%8,%9,%10,%11,%12,%13,%14,%15,%16,%17,%18,%19,%20,%21,%22,%23,%24,%25,%26,%27,%28,%29,%30,%31,%32,%33,%34,%35,%36,%37,%38,%39}, {%40,%41,%42,%43}, %44, p, 1, 1, 0;\n}"
    : "+f"(d[0]),"+f"(d[1]),"+f"(d[2]),"+f"(d[3]),"+f"(d[4]),"+f"(d[5]),"+f"(d[6]),"+f"(d[7]),"+f"(d[8]),"+f"(d[9]),"+f"(d[10]),"+f"(d[11]),"+f"(d[12]),"+f"(d[13]),"+f"(d[14]),"+f"(d[15]),"+f"(d[16]),"+f"(d[17]),"+f"(d[18]),"+f"(d[19]),"+f"(d[20]),"+f"(d[21]),"+f"(d[22]),"+f"(d[23]),"+f"(d[24]),"+f"(d[25]),"+f"(d[26]),"+f"(d[27]),"+f"(d[28]),"+f"(d[29]),"+f"(d[30]),"+f"(d[31]),"+f"(d[32]),"+f"(d[33]),"+f"(d[34]),"+f"(d[35]),"+f"(d[36]),"+f"(d[37]),"+f"(d[38]),"+f"(d[39])
    : "r"(a0), "r"(a1), "r"(a2), "r"(a3), "l"(db), "r"(sd));
}
template <> __device__ __forceinline__ void wgmma_conv<4>(float (&d)[64], uint32_t a0, uint32_t a1, uint32_t a2, uint32_t a3, uint64_t db, int sd) {
  asm volatile("{\n.reg .pred p;\nsetp.ne.b32 p, %37, 0;\n"
    "wgmma.mma_async.sync.aligned.m64n64k16.f32.bf16.bf16 {%0,%1,%2,%3,%4,%5,%6,%7,%8,%9,%10,%11,%12,%13,%14,%15,%16,%17,%18,%19,%20,%21,%22,%23,%24,%25,%26,%27,%28,%29,%30,%31}, {%32,%33,%34,%35}, %36, p, 1, 1, 0;\n}"
    : "+f"(d[0]),"+f"(d[1]),"+f"(d[2]),"+f"(d[3]),"+f"(d[4]),"+f"(d[5]),"+f"(d[6]),"+f"(d[7]),"+f"(d[8]),"+f"(d[9]),"+f"(d[10]),"+f"(d[11]),"+f"(d[12]),"+f"(d[13]),"+f"(d[14]),"+f"(d[15]),"+f"(d[16]),"+f"(d[17]),"+f"(d[18]),"+f"(d[19]),"+f"(d[20]),"+f"(d[21]),"+f"(d[22]),"+f"(d[23]),"+f"(d[24]),"+f"(d[25]),"+f"(d[26]),"+f"(d[27]),"+f"(d[28]),"+f"(d[29]),"+f"(d[30]),"+f"(d[31])
    : "r"(a0), "r"(a1), "r"(a2), "r"(a3), "l"(db), "r"(sd));
}
template <> __device__ __forceinline__ void wgmma_conv<5>(float (&d)[64], uint32_t a0, uint32_t a1, uint32_t a2, uint32_t a3, uint64_t db, int sd) {
  asm volatile("{\n.reg .pred p;\nsetp.ne.b32 p, %29, 0;\n"
    "wgmma.mma_async.sync.aligned.m64n48k16.f32.bf16.bf16 {%0,%1,%2,%3,%4,%5,%6,%7,%8,%9,%10,%11,%12,%13,%14,%15,%16,%17,%18,%19,%20,%21,%22,%23}, {%24,%25,%26,%27}, %28, p, 1, 1, 0;\n}"
    : "+f"(d[0]),"+f"(d[1]),"+f"(d[2]),"+f"(d[3]),"+f"(d[4]),"+f"(d[5]),"+f"(d[6]),"+f"(d[7]),"+f"(d[8]),"+f"(d[9]),"+f"(d[10]),"+f"(d[11]),"+f"(d[12]),"+f"(d[13]),"+f"(d[14]),"+f"(d[15]),"+f"(d[16]),"+f"(d[17]),"+f"(d[18]),"+f"(d[19]),"+f"(d[20]),"+f"(d[21]),"+f"(d[22]),"+f"(d[23])
    : "r"(a0), "r"(a1), "r"(a2), "r"(a3), "l"(db), "r"(sd));
}
template <> __device__ __forceinline__ void wgmma_conv<6>(float (&d)[64], uint32_t a0, uint32_t a1, uint32_t a2, uint32_t a3, uint64_t db, int sd) {
  asm volatile("{\n.reg .pred p;\nsetp.ne.b32 p, %21, 0;\n"
    "wgmma.mma_async.sync.aligned.m64n32k16.f32.bf16.bf16 {%0,%1,%2,%3,%4,%5,%6,%7,%8,%9,%10,%11,%12,%13,%14,%15}, {%16,%17,%18,%19}, %20, p, 1, 1, 0;\n}"
    : "+f"(d[0]),"+f"(d[1]),"+f"(d[2]),"+f"(d[3]),"+f"(d[4]),"+f"(d[5]),"+f"(d[6]),"+f"(d[7]),"+f"(d[8]),"+f"(d[9]),"+f"(d[10]),"+f"(d[11]),"+f"(d[12]),"+f"(d[13]),"+f"(d[14]),"+f"(d[15])
    : "r"(a0), "r"(a1), "r"(a2), "r"(a3), "l"(db), "r"(sd));
}
template <> __device__ __forceinline__ void wgmma_conv<7>(float (&d)[64], uint32_t a0, uint32_t a1, uint32_t a2, uint32_t a3, uint64_t db, int sd) {
  asm volatile("{\n.reg .pred p;\nsetp.ne.b32 p, %13, 0;\n"
    "wgmma.mma_async.sync.aligned.m64n16k16.f32.bf16.bf16 {%0,%1,%2,%3,%4,%5,%6,%7}, {%8,%9,%10,%11}, %12, p, 1, 1, 0;\n}"
    : "+f"(d[0]),"+f"(d[1]),"+f"(d[2]),"+f"(d[3]),"+f"(d[4]),"+f"(d[5]),"+f"(d[6]),"+f"(d[7])
    : "r"(a0), "r"(a1), "r"(a2), "r"(a3), "l"(db), "r"(sd));
}

__device__ __forceinline__ void conv_ld(uint32_t* r, uint32_t a) {
  asm volatile("ld.shared.b32 %0, [%8];\nld.shared.b32 %1, [%8 + 256];\nld.shared.b32 %2, [%8 + 32];\nld.shared.b32 %3, [%8 + 288];\n"
               "ld.shared.b32 %4, [%8 + 512];\nld.shared.b32 %5, [%8 + 768];\nld.shared.b32 %6, [%8 + 544];\nld.shared.b32 %7, [%8 + 800];"
               : "=r"(r[0]), "=r"(r[1]), "=r"(r[2]), "=r"(r[3]), "=r"(r[4]), "=r"(r[5]), "=r"(r[6]), "=r"(r[7]) : "r"(a) : "memory");
}
template <int I> struct Step { static constexpr int value = I; };
template <int I, bool SHRINK> __device__ __forceinline__ void conv_group(float (&acc)[64], const uint32_t (&r)[32], uint64_t db, int sd) {
  wg_fence();
  wgmma_conv<SHRINK ? 2 * I : 0>(acc, r[8 * I], r[8 * I + 1], r[8 * I + 2], r[8 * I + 3], db + 32 * I, I > 0 || sd);
  wgmma_conv<SHRINK ? 2 * I + 1 : 0>(acc, r[8 * I + 4], r[8 * I + 5], r[8 * I + 6], r[8 * I + 7], db + 32 * I + 16, 1);
  wg_commit();
}

struct Params {
  Scratch* s;
  const uint16_t *logdt, *dskip, *b1, *b2, *x, *ssm[6], *w1, *w2;
};

__global__ void __cluster_dims__(2, 1, 1) __launch_bounds__(512, 1)
fused_kernel(const __grid_constant__ Params p, const __grid_constant__ Maps maps) {
  extern __shared__ __align__(1024) uint8_t smem_raw[];
  const uint32_t sb = s2u(smem_raw);
  const uint32_t bars = sb + SM_BAR;
  const int tid = threadIdx.x, lane = tid & 31, g = lane >> 2, t = lane & 3, tq = tid & 127;
  const int wid = __shfl_sync(~0u, tid >> 5, 0), wgi = wid >> 2, warp = wid & 3;
  const int b = blockIdx.x, rank = b & 1, cl = b >> 1;
  const int mt = cl & 15, nt = cl >> 4;
  const int js = 4 * rank + nt;
  const int krot = (mt >> 3) * 320;

  auto load_x = [&](int kb, int s) {
    mbar_expect(bars + 8 * (BAR_AFULL + s), 16384);
    tma2d(sb + SM_A + s * SLOT, &maps.x128, bars + 8 * (BAR_AFULL + s), kb * 64 + (kb < 5 ? krot : -krot), mt * 128);
  };
  auto load_w1 = [&](int i, int s) {
    const uint32_t d = sb + SM_B + s * SLOT, fb = bars + 8 * (BAR_BFULL + s);
    const int k0 = i * 32 + (i < 10 ? krot : -krot);
    mbar_expect(fb, 32 * 216 * 2);
    tma3d(d, &maps.w1, fb, 0, k0, 3 * js);
    tma2d(d + 12288, &maps.w1n, fb, 1536 + 24 * js, k0);
  };
  asm volatile("setmaxnreg.dec.sync.aligned.u32 %0;" ::"n"(REG_0));
  if (wgi == 3) {
    const bool el = elect();
    if (el) {
#pragma unroll
      for (int i = 0; i < 8; i++) mbar_init(bars + 128 * warp + 8 * i, 1);
      asm volatile("fence.mbarrier_init.release.cluster;" ::: "memory");
      if (warp == 3) {
        mbar_expect(bars + 8 * BAR_PAR, 6 * 1280);
#pragma unroll
        for (int i = 0; i < 6; i++) bulk_g2s(sb + SM_PAR + i * 1280, p.ssm[i] + b * 5 * NST, 1280, bars + 8 * BAR_PAR);
      }
#pragma unroll
      for (int i = 8; i < 16; i++) mbar_init(bars + 128 * warp + 8 * i, warp == 3 ? 4 : (XMC && i < 11 && warp == 0) ? 16 : 8);
      asm volatile("fence.mbarrier_init.release.cluster;" ::: "memory");
      if (warp == 0) {
        const unsigned t0 = clock();
        while ((unsigned)clock() - t0 < LNXD) {}
        mbar_expect(bars + 8 * BAR_LNX, 16 * DM * 2);
        bulk_g2s(sb + SM_LNT, p.x + (size_t)b * 16 * DM, 16 * DM * 2, bars + 8 * BAR_LNX);
        TRACE(29);
        if (W1PF == 1) asm volatile("cp.async.bulk.prefetch.L2.global [%0], %1;" ::"l"((const char*)p.w1 + (size_t)b * 17280), "r"(17280) : "memory");
      }
    }
    __syncwarp();
    const unsigned ep0 = ld_relaxed(p.s->epoch);
    asm volatile("bar.arrive 0, 512;" ::: "memory");
    cluster_arrive();
    bar_sync(1);
    if (XMC && warp == 2) cluster_wait();
    if (el && (warp == 1 || warp == 2)) {
      mbar_wait(bars + 8 * BAR_PAR, 0);
#pragma unroll 1
      for (int i = 0; i < 5 - warp; i++) {
        if (warp == 2) load_x(i, i); else load_w1(i, i);
      }
      TRACE(30);
    }
    if (W1PF == 2 && el && warp == 3) {
      mbar_wait(bars + 8 * BAR_PAR, 0);
      asm volatile("cp.async.bulk.prefetch.L2.global [%0], %1;" ::"l"((const char*)p.w1 + (size_t)b * 17280), "r"(17280) : "memory");
    }
    __syncwarp();
    {
      const uint32_t xr = sb + SM_LNT + (8 * (warp & 1) + g) * (DM * 2);
      uint4 xv[10];
      mbar_wait(bars + 8 * BAR_LNX, 0);
      if (tq == 0) TRACE(35);
#pragma unroll
      for (int i = 0; i < 10; i++) xv[i] = lds128(xr + (warp >> 1) * DM + t * 16 + i * 64);
      const uint32_t pv_ = lds16(xr);
      const uint32_t* w = reinterpret_cast<const uint32_t*>(xv);
      float sq[3][4] = {};
      const uint32_t npv = (pv_ ^ 0x8000u) * 0x10001u;
#pragma unroll
      for (int i = 0; i < 40; i++)
        asm("mma.sync.aligned.m16n8k8.row.col.f32.bf16.bf16.f32 {%0, %1, %2, %3}, {%4, %5}, {%4}, {%0, %1, %2, %3};"
            : "+f"(sq[i % 3][0]), "+f"(sq[i % 3][1]), "+f"(sq[i % 3][2]), "+f"(sq[i % 3][3]) : "r"(hadd2(w[i], npv)), "r"(0x3f803f80u));
      if (tq == 0) TRACE(13);
#pragma unroll
      for (int q = 0; q < 4; q++) sq[0][q] += sq[1][q] + sq[2][q];
      if (t == (g >> 1)) sts64(sb + SM_LNS + warp * 64 + g * 8, __float_as_uint((g & 1) ? sq[0][3] : sq[0][2]), __float_as_uint((g & 1) ? sq[0][1] : sq[0][0]));
      bar_sync(1);
      const float2 o1 = lds64f(sb + SM_LNS + warp * 64 + g * 8), o2 = lds64f(sb + SM_LNS + (warp ^ 2) * 64 + g * 8);
      const float s0 = (o1.x + o2.x) * (1.f / DM);
      const float var = fmaxf(fmaf(-s0, s0, (o1.y + o2.y) * (1.f / DM)), 0.f), mean = bf_lo(pv_) + s0;
      const float m1 = bf_round(mean), r1 = rcp_std(var), rh = bf_round(r1);
      const uint32_t nm = pack_bf16(-m1, -m1), rh2 = pack_bf16(rh, rh), rl2 = pack_bf16(r1 - rh, r1 - rh);
      const uint32_t dst = sb + SM_LNT + (warp >> 1) * 10240 + lane * 32 + 16 - (warp & 1) * 16;
#pragma unroll
      for (int i = 0; i < 10; i++) {
        uint32_t r[4];
#pragma unroll
        for (int q = 0; q < 4; q++) { const uint32_t d = hadd2(w[4 * i + q], nm); r[q] = hfma2(d, rh2, hmul2(d, rl2)); }
        stsm4t(dst + i * 1024, r);
      }
      const float m2 = bf_round((mean - m1) * r1), r2 = 0.5f * rcp_std(var * r1 * r1);
      if (t == 0 && warp < 2) p.s->stats[16 * b + 8 * warp + g] = make_float2(r1 * r2, -(m1 * r1 + m2) * r2);
      bar_sync(1);
      if (tq == 0) TRACE(16);
    }
    asm volatile("setmaxnreg.dec.sync.aligned.u32 %0;" ::"n"(REG_P));
    if (el) {
      unsigned* hc = p.s->hcnt + (HGLOB ? 0 : 32 * mt + (HRK ? 16 * rank : 0));
      auto seg_first = [&](int sg) {
        const int f = sg < 5 ? sg - 2 : sg - 5;
        return sg == 0 ? 6 * js + 5 : sg == 1 ? 50 + 3 * rank : 24 * rank + 6 * (f + (f >= nt)) + (sg < 5 ? 5 : 3);
      };
      auto seg_count = [](int sg) { return (0x44422236 >> (4 * sg)) & 15; };
      if (warp == 0) {
        int s = 0, ph = 0;
#pragma unroll 1
        for (int kb = NA; kb < 10; kb++) {
          if (XMC) mbar_wait_cluster(bars + 8 * (BAR_AEMPTY + s), ph); else mbar_wait(bars + 8 * (BAR_AEMPTY + s), ph);
          load_x(kb, s);
          if (++s == NA) { s = 0; ph ^= 1; }
        }
        const unsigned ep = ep0 + 1;
        s = 6; ph = 1;
#pragma unroll 1
        for (int sg = 1; sg < 8; sg++) {
          if (sg < 4) mbar_wait(bars + 8 * (BAR_HRD1 - 1 + sg), 0);
          if ((sg & 3) == 1) {
            poll_ge(hc + 128 * (sg - 1), (HGLOB ? NCTA : HRK ? 4 : 8) * ep);
            fence_async_global();
            TRACE(32 + (sg >> 2));
          }
          const uint16_t* src = p.s->H + (size_t)(mt * 54 + seg_first(sg)) * 4096;
          int n = seg_count(sg);
#pragma unroll 1
          do {
            mbar_wait(bars + 8 * (BAR_REMPTY2 + s), ph);
            bulk_g2s(sb + s * RSLOT, src, 8192, bars + 8 * (BAR_RFULL2 + s));
            src -= 4096;
            if (++s == NR) { s = 0; ph ^= 1; }
          } while (--n);
        }
        const int row0 = mt * 128 + rank * 64;
        const uint32_t fb = bars + 8 * BAR_FIN;
        mbar_wait(bars + 8 * BAR_CVD, 0);
        mbar_expect(fb, 16384 + 4096 + 20480);
        tma2d(sb + SM_FX, &maps.x64, fb, nt * 128, row0);
        tma2d(sb + SM_FX + 8192, &maps.x64, fb, nt * 128 + 64, row0);
        tma2d(sb + SM_FXN, &maps.x32, fb, 512 + 32 * nt, row0);
        if (CVG) poll_ge(p.s->cvcnt + 8 * nt, 160 * ep); else poll_ge(p.s->cvcnt, NCTA * ep);
        fence_async_global();
        tma2d(sb + SM_FZ, &maps.z128, fb, SEQ - 64 - row0, nt * 128);
        tma2d(sb + SM_FZ + 16384, &maps.z32, fb, SEQ - 64 - row0, 512 + 32 * nt);
      } else if (warp == 1) {
        int s = 4, ph = 1;
        mbar_wait(bars + 8 * BAR_KGD, 0);
        fence_async_smem();
#pragma unroll 1
        for (int i = B45 ? 6 : 4; i < 20; i++) {
          mbar_wait(bars + 8 * (BAR_BEMPTY + s), ph);
          load_w1(i, s);
          if (++s == NB) { s = 0; ph ^= 1; }
        }
        mbar_wait(bars + 8 * BAR_G1FREE, 0);
        s = 0; ph = 1;
#pragma unroll 1
        for (int sg = 0; sg < 8; sg++) {
          int row = seg_first(sg) * 32, n = seg_count(sg);
#pragma unroll 1
          do {
            mbar_wait(bars + 8 * (BAR_REMPTY2 + s), ph);
            const uint32_t d = sb + s * RSLOT, fb = bars + 8 * (BAR_RFULL2 + s);
            mbar_expect(fb, sg ? 18432 : 10240);
            tma3d(d + 8192, &maps.w2, fb, 0, row, 2 * nt);
            tma2d(d + 16384, &maps.w2n, fb, 512 + 32 * nt, row);
            row -= 32;
            if (++s == NR) { s = 0; ph ^= 1; }
          } while (--n);
        }
      } else if (warp == 2) {
        mbar_expect(bars + 8 * BAR_RECV, 20480);
        mbar_wait(bars + 8 * BAR_ST, 0);
        red_release(p.s->stcnt);
        TRACE(8);
        poll_ge(p.s->stcnt, NCTA * (ep0 + 1));
                fence_async_global();
        mbar_expect(bars + 8 * BAR_TAB, 1728 + 1024);
        bulk_g2s(sb + SM_COL, p.s->col + ((ep0 & 1) * 8 + js) * 432, 1728, bars + 8 * BAR_TAB);
        bulk_g2s(sb + SM_ROW, p.s->stats + mt * 128, 1024, bars + 8 * BAR_TAB);
        TRACE(27);
        uint16_t* Hm = p.s->H + (size_t)mt * 54 * 4096;
        mbar_wait(bars + 8 * BAR_HC, 0);
        fence_async_smem();
#pragma unroll 1
        for (int i = 0; i < 6; i++) {
          const int ch = 192 + 3 * js + (i >> 1);
          bulk_s2g(Hm + (ch >> 2) * 4096 + (i & 1) * 2048 + (ch & 3) * 512, sb + 6 * RSLOT + (i & 1) * 4096 + (i >> 1) * 1024, 1024);
        }
#pragma unroll 1
        for (int i = 0; i < 6; i++) {
          bulk_commit();
          mbar_wait(bars + 8 * (BAR_HC + (i < 4 ? 1 + (i >> 1) : i - 1)), 0);
          fence_async_smem();
          bulk_wait_read<HPACE>();
          if (i == 2 + HPACE || i == 4 + HPACE) mbar_arrive(bars + 8 * (BAR_HRD1 - 1 + ((i - HPACE) >> 1)));
          bulk_s2g(Hm + (6 * js + 5 - i) * 4096, sb + i * RSLOT, 8192);
          if (i == 2) {
            bulk_wait<0>();
            red_after_bulk(hc);
            TRACE(62);
          }
        }
        bulk_commit();
        bulk_wait_read<0>();
        mbar_arrive(bars + 8 * (BAR_HRD1 + 2));
        bulk_wait<0>();
        red_after_bulk(hc + 512);
        TRACE(63);
      } else {
        const unsigned ep = ep0 + 1;
        fence_async_smem();
        bulk_s2g(p.s->xnT + (size_t)(127 - b) * (DM * 16), sb + SM_LNT, DM * 32);
        bulk_commit();
        bulk_wait<0>();
        red_after_bulk(p.s->xncnt);
        TRACE(17);
        asm volatile("cp.async.bulk.prefetch.L2.global [%0], %1;" ::"l"((const char*)p.w2 + (size_t)b * 17280), "r"(17280) : "memory");
        poll_ge(p.s->xncnt, NCTA * ep);
        fence_async_global();
        TRACE(11);
#pragma unroll 1
        for (int c = 0; c < 5; c++) {
          const int d = b * 5 + c;
          mbar_expect(bars + 8 * (BAR_UFULL + c), 129 * 32);
          tma2d(sb + SM_UBUF + c * U_SZ, &maps.xt, bars + 8 * (BAR_UFULL + c), ((d & ~30) | ((d & 6) << 2) | ((d & 24) >> 2)) * 16, 0);
        }
#pragma unroll 1
        for (int c = 0; c < 5; c++) {
          mbar_wait(bars + 8 * (BAR_ZRDY + c), 0);
          fence_async_smem();
          bulk_s2g(p.s->zT + (size_t)(b * 5 + c) * SEQ, sb + SM_UBUF + (c - 1) * U_SZ, 4096);
          bulk_commit();
        }
        bulk_wait<0>();
        if (CVG) {
          const int d0 = 5 * b, lim = d0 < 512 ? (d0 | 127) + 1 : (d0 | 31) + 1, n0 = min(lim - d0, 5);
          const int g0 = d0 < 512 ? d0 >> 7 : (d0 - 512) >> 5, g1 = lim < 512 ? lim >> 7 : (lim - 512) >> 5;
          fence_async_global();
          asm volatile("red.relaxed.gpu.global.add.u32 [%0], %1;" ::"l"(p.s->cvcnt + 8 * g0), "r"(n0) : "memory");
          if (n0 < 5) asm volatile("red.relaxed.gpu.global.add.u32 [%0], %1;" ::"l"(p.s->cvcnt + 8 * g1), "r"(5 - n0) : "memory");
        } else red_after_bulk(p.s->cvcnt);
        mbar_arrive(bars + 8 * BAR_CVD);
        TRACE(12);
        asm volatile("barrier.cluster.wait.acquire;" ::: "memory");
        asm volatile("mbarrier.arrive.release.cluster.shared::cluster.b64 _, [%0];" ::"r"(mapa(bars + 8 * BAR_RRDY, rank ^ 1)) : "memory");
      }
    }
    return;
  }

  uint32_t kq[3][4];
#pragma unroll
  for (int k = 0; k < 3; k++) kq[k][3] = ldg16v(p.logdt + b * 5 + wgi + k);
  const uint32_t aux16 = ldg16v(wgi == 2 ? (tq & 1 ? p.b2 : p.dskip) + b * 5 + (tq < 10 ? tq >> 1 : 0)
                                         : p.b1 + (tid < 192 ? 192 * js + tid : tid < 216 ? 1344 + 24 * js + tid : 0));
  const unsigned ep0 = ld_relaxed(p.s->epoch);
  asm volatile("bar.sync 0, 512;" ::: "memory");
  cluster_arrive();
  if (tid == 0) TRACE(28);
  mbar_wait(bars + 8 * BAR_PAR, 0);
  if (tid == 0) TRACE(36);
#pragma unroll
  for (int k = 0; k < 3; k++) {
    const uint32_t pp = sb + SM_PAR + (wgi + k) * 256 + tq * 2;
#pragma unroll
    for (int j = 0; j < 3; j++) kq[k][j] = prmt(lds16(pp + 2 * j * 1280), lds16(pp + (2 * j + 1) * 1280), 0x5410);
  }
  asm volatile("bar.sync 6, 384;" ::: "memory");
  {
    const int nr = wgi == 2 ? 3 : 1;
#pragma unroll 1
    for (int r = 0; r < nr; r++) {
      const uint32_t buf = sb + (wgi + r == 2 ? SM_B + 4 * SLOT : wgi ? SM_KG1 + KG_SZ : SM_KG1);
      if (r == 1) mbar_wait(bars + 8 * BAR_KG01, 0);
      const float dt = bf_round(__expf(bf_lo(kq[0][3])));
      const float ar2 = dt * bf_lo(kq[0][0]) * 1.4426950408889634f, at = dt * bf_hi(kq[0][0]) * 0.15915494309189535f;
      const cpx cb = cmul(cpx{bf_lo(kq[0][2]), -bf_hi(kq[0][2])}, cpx{dt * bf_lo(kq[0][1]), -dt * bf_hi(kq[0][1])});
#pragma unroll
      for (int j = 0; j < 4; j++) { kq[0][j] = kq[1][j]; kq[1][j] = kq[2][j]; }
      const cpx e1 = cexp_x(ar2, -at, 1.f), e8 = cexp_x(ar2, at, 8.f), e256 = cexp_x(ar2, -at, 256.f);
      uint32_t qa = buf + ((tq & 63) >> 2) * KG_LBO_A + (tq >> 6) * 512 + (tq & 3) * 4;
      cpx v[4];
      v[0] = {1.f, 0.f}; v[1] = e8; v[2] = cmul(e8, e8); v[3] = cmul(v[2], e8);
      const cpx e32 = cmul(v[2], v[2]);
#pragma unroll 2
      for (int i = 0; i < 8; i++) {
#pragma unroll
        for (int q = 0; q < 4; q++) {
          sts32(qa + q * 16, pack_bf16(v[q].r, v[q].i));
          v[q] = cmul(v[q], e32);
        }
        qa += 64;
      }
      const uint32_t pa = buf + KG_B + ((tq & 63) >> 2) * KG_LBO_B + (tq >> 6) * 384 + (tq & 3) * 4;
      const cpx e2 = cmul(e1, e1), e4 = cmul(e2, e2), e512 = cmul(e256, e256);
      auto putp = [&](int pi, cpx z) { sts32(pa + pi * 16, pack_bf16(z.r, z.i)); };
      cpx x0 = cb, x1 = cmul(cb, e1);
      putp(0, x0); putp(1, x1);
#pragma unroll
      for (int i = 1; i < 4; i++) { x0 = cmul(x0, e2); x1 = cmul(x1, e2); putp(2 * i, x0); putp(2 * i + 1, x1); }
      cpx y = cmul(cb, e256), z = cmul(cb, e512);
      putp(8, y); putp(12, z); putp(13, cmul(z, e4));
      { const cpx w = cmul(y, e2); putp(9, w); putp(11, cmul(w, e4)); putp(10, cmul(y, e4)); }
      y = cmul(y, e512); z = cmul(z, e512);
      putp(14, y); putp(15, cmul(y, e4)); putp(16, z);
      y = cmul(y, e512); z = cmul(z, e512);
      putp(17, y); putp(18, z);
      putp(19, cmul(y, e512)); putp(20, cmul(z, e512));
      fence_async_smem();
      if (tq == 0 && r == 0) TRACE(wgi == 2 ? 26 : 25);
      bar_sync(2 + wgi);
      float ka[24];
      const uint64_t da = mkdesc(opaque(buf), KG_LBO_A, 128, 0), db = da - (((KG_LBO_A - KG_LBO_B) << 12) - KG_B / 16);
      wg_fence();
#pragma unroll
      for (int ks = 0; ks < 8; ks++) wgmma_kg48(ka, da + ks * (2 * KG_LBO_A / 16), db + ks * (2 * KG_LBO_B / 16), ks > 0);
      wg_commit();
      wg_wait<0>();
      reg_fence(ka);
      const uint32_t cm = buf + (lane >> 4) * KG_LBO_A + (warp | 2) * 256 + (lane & 15) * 16;
      if (warp >= 2) {
#pragma unroll
        for (int q = 0; q < 3; q++)
          sts128(cm + q * 2 * KG_LBO_A, __float_as_uint(ka[12 + 4 * q]), __float_as_uint(ka[13 + 4 * q]), __float_as_uint(ka[14 + 4 * q]), __float_as_uint(ka[15 + 4 * q]));
      }
      bar_sync(2 + wgi);
      if (warp < 2) {
        const uint32_t tp = sb + SM_TAPS + (wgi + r) * TAPS_SZ;
        const float4 o0 = lds128f(cm), o1 = lds128f(cm + 2 * KG_LBO_A), o2 = lds128f(cm + 4 * KG_LBO_A);
        const int i = 16 * warp + g;
        const uint32_t a0 = tp + 16 * i + 4 * t, a1 = tp + (t < 2 ? 512 + 8 * i + 4 * t : 512 + 128 * t + 4 * i), a2 = tp + 1024 + 128 * t + 2 * i;
        sts32(a0, pack_bf16(ka[0] + o0.x, ka[1] + o0.y));
        sts32(a0 + 128, pack_bf16(ka[2] + o0.z, ka[3] + o0.w));
        sts32(a1, pack_bf16(ka[4] + o1.x, ka[5] + o1.y));
        sts32(a1 + (t < 2 ? 64 : 32), pack_bf16(ka[6] + o1.z, ka[7] + o1.w));
        const uint32_t l0 = pack_bf16(ka[8] + o2.x, ka[9] + o2.y), l1 = pack_bf16(ka[10] + o2.z, ka[11] + o2.w);
        if (t < 2 || (t == 2 && i == 0)) sts16(a2, l0);
        if (t < 2) { sts16(a2 + 64, l0 >> 16); sts16(a2 + 16, l1); sts16(a2 + 80, l1 >> 16); }
      }
      bar_sync(2 + wgi);
      if (lane == 0 && r == 0) mbar_arrive(bars + 8 * (wgi == 2 ? BAR_KGD : BAR_KG01));
      if (tid == 256) TRACE(44 + 2 * r);
    }
    if (tq == 0) TRACE(wgi == 2 ? 9 : 14);
  }

  if (wgi == 2) {
    asm volatile("setmaxnreg.inc.sync.aligned.u32 %0;" ::"n"(REG_A));
    auto expand = [&](int c, auto quarter) {
      constexpr int i = decltype(quarter)::value;
      const uint32_t tp = sb + SM_TAPS + min(c, 4) * TAPS_SZ, ke = sb + SM_KEXP + (c & 1) * KEXP_SZ + 64 + 2048 * i + 16 * tq;
      if (i == 0) {
        const bool lo = tq < 64;
        const uint32_t a = tp + (lo ? 8 * tq : 256 + 4 * tq);
        const uint32_t k0 = lds32(a - 4), k1 = lds32(a), k2 = lds32(a + 4);
        sts128(ke, prmt(k1, tq ? k0 : 0u, tq <= 64 ? 0x7610 : 0x1010), prmt(k1, k1, lo ? 0x1032 : 0x1010), prmt(k2, k1, lo ? 0x7610 : 0x5476),
               prmt(k2, k1, lo ? 0x1032 : 0x7610));
      } else if (i == 1) {
        const uint32_t j = lds16(tp + 768 + 2 * tq), u = lds16(tp + 770 + 2 * tq), m = (tq & 1) ? u : j, jj = prmt(j, j, 0x1010);
        sts128(ke, jj, jj, prmt(m, j, 0x5410), prmt(u, m, 0x5410));
      } else {
        const uint32_t a = tp + 768 + 128 * i + (tq & ~1);
        const uint32_t l = lds16(a), u = lds16(a + 2 * (tq & 1)), m = (tq & 2) ? u : l, uu = prmt(u, u, 0x1010);
        sts128(ke, prmt(m, l, 0x5410), prmt(u, m, 0x5410), uu, uu);
      }
    };
    auto reduce = [&](int k) {
      const int c = k >> 1;
      const float2 sc = lds64f(sb + SM_SC + 8 * c);
      const uint32_t dsk = __float_as_uint(sc.x), b2 = __float_as_uint(sc.y);
      const uint32_t ea = sb + SM_EXCH + (k & 1) * 8192 + (4 * warp + t) * 128 + ((g + 2 * t) & 7) * 16;
      const uint32_t ua = sb + SM_UBUF + c * U_SZ + (~k & 1) * 2048 + (8 * warp + (lane & 7)) * 16 + (lane & 24) * 64;
      const uint4 e0 = lds128(ea), e1 = lds128(ea + 2048), e2 = lds128(ea + 4096), e3 = lds128(ea + 6144);
      uint32_t uu[4], o[4];
      ldsm4t(uu, ua);
      o[0] = hadd2(hadd2(e0.x, e1.x), hadd2(e2.x, e3.x)); o[1] = hadd2(hadd2(e0.y, e1.y), hadd2(e2.y, e3.y));
      o[2] = hadd2(hadd2(e0.z, e1.z), hadd2(e2.z, e3.z)); o[3] = hadd2(hadd2(e0.w, e1.w), hadd2(e2.w, e3.w));
#pragma unroll
      for (int q = 0; q < 4; q++) o[q] = hadd2(hadd2(o[q], hmul2(uu[q], dsk)), b2);
      stsm4t(ua - U_SZ, o);
    };
    auto z_ready = [&](int c) {
      __syncwarp();
      if (lane == 0) mbar_arrive(bars + 8 * (BAR_ZRDY + c));
    };
    if (tq < 10) sts32(sb + SM_SC + 4 * tq, aux16 * 0x10001u);
    if (tq < 8) sts128(sb + SM_KEXP + (tq >> 2) * KEXP_SZ + (tq & 3) * 16, 0, 0, 0, 0);
    expand(0, Step<0>()); expand(0, Step<1>()); expand(0, Step<2>()); expand(0, Step<3>());
    bar_sync(4);
    if (tq == 0) TRACE(10);
    float cy0 = 0.f, cy1 = 0.f;
    uint32_t cyw = 0, r[32];
    const uint32_t kx0 = sb + SM_KEXP + 4 * (16 + 16 * warp + g - 2 * t);
    conv_ld(r, kx0); conv_ld(r + 8, kx0 + 1024); conv_ld(r + 16, kx0 + 2048);
#pragma unroll 1
    for (int k = 0; k < 10; k++) {
      const int c = k >> 1, lo = k & 1;
      const uint32_t kx = kx0 + (c & 1) * KEXP_SZ + lo * 4096;
      const uint64_t db = mkdesc(sb + SM_UBUF + c * U_SZ, 16, 128, 0);
      float acc[64];
      if (tq == 0 && k >= 5 && k < 9) TRACE(51 + k);
      if (tq == 0) TRACE(k == 2 * TC ? 18 : k == 2 * TC + 1 ? 20 : k == 2 * TC + 2 ? 19 : 61);
      if (lo) {
        conv_group<0, false>(acc, r, db, 0);
        expand(c + 1, Step<0>());
        conv_group<1, false>(acc, r, db, 0);
        expand(c + 1, Step<1>());
        wg_wait<1>();
        conv_ld(r, kx);
        conv_group<2, false>(acc, r, db, 0);
        expand(c + 1, Step<2>());
        wg_wait<1>();
        conv_ld(r + 8, kx + 1024);
        conv_group<3, false>(acc, r, db, 0);
        expand(c + 1, Step<3>());
        wg_wait<1>();
        conv_ld(r + 16, kx + 2048);
      } else {
        mbar_wait(bars + 8 * (BAR_UFULL + c), 0);
        if (tq == 0 && k == 0) TRACE(3);
      }
      conv_group<0, true>(acc, r, db + 128, lo);
      bar_sync(4);
      wg_wait<1>();
      conv_ld(r + 24, kx + 3072);
      conv_group<1, true>(acc, r, db + 128, 1);
      conv_group<2, true>(acc, r, db + 128, 1);
      conv_group<3, true>(acc, r, db + 128, 1);
      reduce(k - 1);
      wg_wait<0>();
      reg_fence(acc);
      if (lo) {
        const uint32_t kn = kx0 + (~c & 1) * KEXP_SZ;
        conv_ld(r, kn); conv_ld(r + 8, kn + 1024); conv_ld(r + 16, kn + 2048);
      }
      const uint32_t ea = sb + SM_EXCH + lo * 8192 + warp * 2048 + (t - warp) * 128 + ((g + 2 * (t - warp)) & 7) * 16;
      auto W = [&](int j) { return pack_bf16(acc[4 * j] + (j < 15 ? acc[4 * j + 6] : cy0), acc[4 * j + 1] + (j < 15 ? acc[4 * j + 7] : cy1)); };
      const bool pz = t >= warp;
      const uint32_t w0 = W(0), w4 = W(4), w8 = W(8), w12 = W(12);
      sts128(ea + (pz ? 0 : 2048), pz ? w0 : w4, pz ? w4 : w8, pz ? w8 : w12, pz ? w12 : cyw);
#pragma unroll
      for (int j = 1; j < 4; j++) sts128(ea + j * 512, W(j), W(j + 4), W(j + 8), W(j + 12));
      cy0 = lo ? 0.f : acc[2]; cy1 = lo ? 0.f : acc[3]; cyw = lo ? 0u : w0;
      if (!lo && k) z_ready(c - 1);
    }
    if (tq == 0) TRACE(50);
    bar_sync(4);
    reduce(9);
    z_ready(4);
    if (tq == 0) TRACE(51);
  } else {
    asm volatile("setmaxnreg.inc.sync.aligned.u32 %0;" ::"n"(REG_C));
    {
      float acc[108];
      const uint64_t da0 = mkdesc(sb + SM_A + wgi * 8192, 16, 1024, 1), db0 = mkdesc(sb + SM_B, 4096, 1024, 1);
      int sa = 0, pa = 0, sbi = 0, pb = 0;
      uint32_t relA = 0, relB = 0, relA2 = 0, relB2 = 0;
      if (tid == 0) TRACE(23);
#pragma unroll 1
      for (int i = 0; i < 20; i++) {
        if (!(i & 1)) mbar_wait(bars + 8 * (BAR_AFULL + sa), pa);
        mbar_wait(bars + 8 * (BAR_BFULL + sbi), pb);
        if (tid == 0 && (i == 0 || i == 4 || i == 10)) TRACE(i == 0 ? 0 : i == 4 ? 37 : 38);
        const uint64_t da = da0 + (sa * (SLOT / 16) + (i & 1) * 4), db = db0 + sbi * (SLOT / 16);
        wg_fence();
        wgmma_g1a(acc, da, db, i);
        wgmma_g1b(acc, da, db + 512, i);
        wgmma_g1a(acc, da + 2, db + 128, 1);
        wgmma_g1b(acc, da + 2, db + 640, 1);
        wg_commit();
        if (i < 10 && (i & 7) == (mt & 7)) {
          if (tid == 0 && i >= 2) TRACE(41);
          const int rg = tid & 7, ch = min(tid >> 3, 26);
          float cs[8] = {};
          const uint32_t a = sb + SM_B + sbi * SLOT + (ch >> 3) * 4096 + rg * 128 + (((ch & 7) ^ rg) << 4);
#pragma unroll
          for (int q = 0; q < 4; q++) {
            const uint4 v = lds128(a + q * 1024);
            cs[0] += bf_lo(v.x); cs[1] += bf_hi(v.x); cs[2] += bf_lo(v.y); cs[3] += bf_hi(v.y);
            cs[4] += bf_lo(v.z); cs[5] += bf_hi(v.z); cs[6] += bf_lo(v.w); cs[7] += bf_hi(v.w);
          }
#pragma unroll
          for (int q = 0; q < 4; q++) { const float o = __shfl_xor_sync(~0u, (rg & 4) ? cs[q] : cs[q + 4], 4); cs[q] = ((rg & 4) ? cs[q + 4] : cs[q]) + o; }
#pragma unroll
          for (int q = 0; q < 2; q++) { const float o = __shfl_xor_sync(~0u, (rg & 2) ? cs[q] : cs[q + 2], 2); cs[q] = ((rg & 2) ? cs[q + 2] : cs[q]) + o; }
          { const float o = __shfl_xor_sync(~0u, (rg & 1) ? cs[0] : cs[1], 1); cs[0] = ((rg & 1) ? cs[1] : cs[0]) + o; }
          if (tid == 0 && i >= 2) TRACE(43);
          if (tid < 216) {
            float* cp = p.s->col + js * 432 + (tid >> 1) * 4 + (tid & 1);
            atomicAdd(cp + (ep0 & 1) * 3456, cs[0]);
            if (mt == 2) cp[(ep0 & 1) * 3456 + 2] = 0.5f * bf_lo(aux16);
            if (mt == 3) cp[(~ep0 & 1) * 3456] = 0.f;
          }
          __syncwarp();
          if (lane == 0 && i >= 2) mbar_arrive(bars + 8 * BAR_ST);
          if (tid == 0 && i >= 2) TRACE(42);
        }
        if (i < G1D) wg_wait<2>(); else if (i < G1Y) wg_wait<1>(); else wg_wait<0>();
        if (lane == 0 && i > 1) {
          mbar_arrive(relB2);
          if (i & 1) mbar_arrive(relA2);
        }
        relB2 = relB; relA2 = relA;
        relB = bars + 8 * (BAR_BEMPTY + sbi);
        relA = bars + 8 * (BAR_AEMPTY + sa);
        if (++sbi == NB) { sbi = 0; pb ^= 1; }
        if ((i & 1) && ++sa == NA) { sa = 0; pa ^= 1; }
      }
      wg_wait<0>();
      reg_fence(acc);
      if (lane == 0) mbar_arrive(bars + 8 * BAR_G1FREE);
      if (tid == 0) TRACE(1);
      mbar_wait(bars + 8 * BAR_TAB, 0);
      mbar_wait(bars + 8 * BAR_G1FREE, 0);
      if (tid == 0) TRACE(2);
      const float2 s0 = lds64f(sb + SM_ROW + (wgi * 64 + warp * 16 + g) * 8), s1 = lds64f(sb + SM_ROW + (wgi * 64 + warp * 16 + g + 8) * 8);
      const uint32_t hs = sb + wgi * 4096 + (lane >> 4) * 1024 + warp * 256 + (lane & 15) * 16;
      const uint32_t ca = sb + SM_COL + t * 16;
      uint32_t h[4];
      float2 cc[27], cb[27];
#pragma unroll
      for (int jb = 26; jb > 26 - GPF; jb--) { cc[jb] = lds64f(ca + jb * 64); cb[jb] = lds64f(ca + jb * 64 + 8); }
#pragma unroll
      for (int jb = 26; jb >= 0; jb--) {
        if (jb >= GPF) { cc[jb - GPF] = lds64f(ca + (jb - GPF) * 64); cb[jb - GPF] = lds64f(ca + (jb - GPF) * 64 + 8); }
        const float2 c = cc[jb], d = cb[jb];
        h[2 * (jb & 1)] = gelu_pair(fmaf(s0.x, acc[4 * jb], fmaf(s0.y, c.x, d.x)), fmaf(s0.x, acc[4 * jb + 1], fmaf(s0.y, c.y, d.y)));
        h[2 * (jb & 1) + 1] = gelu_pair(fmaf(s1.x, acc[4 * jb + 2], fmaf(s1.y, c.x, d.x)), fmaf(s1.x, acc[4 * jb + 3], fmaf(s1.y, c.y, d.y)));
        if (jb == 26) stsm2(hs + 6 * RSLOT + 2048, h[0], h[1]);
        else if (!(jb & 1)) stsm4_free(hs + (jb == 24 ? 6 : 5 - (jb >> 2)) * RSLOT + (jb & 2) * 1024, h);
        if ((jb & 7) == 0 || jb == 4) {
          if (jb == 0) fence_async_smem();
          __syncwarp();
          if (lane == 0) asm volatile("mbarrier.arrive.shared::cta.b64 _, [%0];" ::"r"(bars + 8 * (BAR_HC + (jb == 0 ? 4 : jb == 4 ? 3 : 3 - (jb >> 3)))));
        }
      }
      if (tid == 0) TRACE(24);
    }
    bar_sync(2 + wgi);
    float acc[80];
    {
      const uint64_t da0 = mkdesc(sb + wgi * 4096, 1024, 128, 0), db0 = mkdesc(sb + 8192, 4096, 1024, 1);
      int s = 0, ph = 0;
      uint32_t rel = 0;
#pragma unroll 1
      for (int q = 0; q < 27; q++) {
        mbar_wait(bars + 8 * (BAR_RFULL2 + s), ph);
        if (tid == 0 && (q == 0 || q == 5 || q == 6 || q == 15 || q == 26)) TRACE(34 + q);
        const uint64_t da = da0 + s * (RSLOT / 16), db = db0 + s * (RSLOT / 16);
        wg_fence();
        wgmma_g2_ss(acc, da, db, q);
        wgmma_g2_ss(acc, da + 128, db + 128, 1);
        wg_commit();
        if (q < G2Z) {
          wg_wait<0>();
          if (lane == 0) mbar_arrive(bars + 8 * (BAR_REMPTY2 + s));
        } else wg_wait<1>();
        if (++s == NR) { s = 0; ph ^= 1; }
      }
    }
    cluster_wait();
    wg_wait<0>();
    reg_fence(acc);
    uint32_t xz[20];
    const uint32_t ho = sb + tq * 16;
    if (wgi != rank) {
      asm volatile("bar.arrive 5, 256;" ::: "memory");
      mbar_wait_cluster(bars + 8 * BAR_RRDY, 0);
      const uint32_t dst = mapa(sb + SM_RECV + tq * 16, rank ^ 1), rb = mapa(bars + 8 * BAR_RECV, rank ^ 1);
      if (tq == 0) TRACE(4);
#pragma unroll
      for (int i = 0; i < 10; i++)
        asm volatile("st.async.weak.shared::cluster.mbarrier::complete_tx::bytes.v4.b32 [%0], {%1, %2, %3, %4}, [%5];"
                     ::"r"(dst + i * 2048), "r"(pack_bf16(acc[8 * i], acc[8 * i + 1])), "r"(pack_bf16(acc[8 * i + 2], acc[8 * i + 3])),
                       "r"(pack_bf16(acc[8 * i + 4], acc[8 * i + 5])), "r"(pack_bf16(acc[8 * i + 6], acc[8 * i + 7])), "r"(rb) : "memory");
      asm volatile("bar.sync 7, 256;" ::: "memory");
#pragma unroll
      for (int i = 0; i < 5; i++) {
        const uint4 v = lds128(ho + i * 2048);
        xz[4 * i] = v.x; xz[4 * i + 1] = v.y; xz[4 * i + 2] = v.z; xz[4 * i + 3] = v.w;
      }
    } else {
      asm volatile("bar.sync 5, 256;" ::: "memory");
#pragma unroll
      for (int i = 5; i < 10; i++)
        sts128(ho + (i - 5) * 2048, pack_bf16(acc[8 * i], acc[8 * i + 1]), pack_bf16(acc[8 * i + 2], acc[8 * i + 3]),
               pack_bf16(acc[8 * i + 4], acc[8 * i + 5]), pack_bf16(acc[8 * i + 6], acc[8 * i + 7]));
      asm volatile("bar.arrive 7, 256;" ::: "memory");
#pragma unroll
      for (int q = 0; q < 20; q++) xz[q] = pack_bf16(acc[2 * q], acc[2 * q + 1]);
    }
    {
      const int j0 = wgi != rank ? 5 : 0;
      const int xr = warp * 16 + (lane & 15);
      const uint32_t xa = sb + SM_FX + xr * 128, xs = ((lane >> 4) ^ (xr & 7)) << 4;
      const uint32_t za = sb + SM_FZ + j0 * 2048 + (lane >> 4) * 1024 + (lane & 7) * 128 + (((7 - 2 * warp - ((lane >> 3) & 1)) ^ (lane & 7)) << 4);
      uint32_t oa[5];
#pragma unroll
      for (int jj = 0; jj < 5; jj++) oa[jj] = xa + ((j0 + jj) >> 2) * 8192 + (xs ^ (((j0 + jj) & 3) << 5));
      mbar_wait(bars + 8 * BAR_FIN, 0);
      if (tq == 0) TRACE(6);
#pragma unroll
      for (int jj = 0; jj < 5; jj++) {
        uint32_t xx[4], zz[4];
        ldsm4(xx, oa[jj]);
        ldsm4t(zz, za + jj * 2048);
#pragma unroll
        for (int q = 0; q < 4; q++) xz[4 * jj + q] = hadd2(hadd2(xx[q], zz[q]), xz[4 * jj + q]);
      }
      if (tq == 0) TRACE(5);
      mbar_wait_cluster(bars + 8 * BAR_RECV, 0);
      if (tq == 0) TRACE(21);
      uint4 e[5];
#pragma unroll
      for (int jj = 0; jj < 5; jj++) e[jj] = lds128(sb + SM_RECV + tq * 16 + (j0 + jj) * 2048);
#pragma unroll
      for (int jj = 0; jj < 5; jj++) {
        const uint32_t o[4] = {hadd2(xz[4 * jj], e[jj].x), hadd2(xz[4 * jj + 1], e[jj].y), hadd2(xz[4 * jj + 2], e[jj].z), hadd2(xz[4 * jj + 3], e[jj].w)};
        stsm4_free(oa[jj], o);
      }
      asm volatile("bar.sync 5, 256;" ::: "memory");
      if (tid == 0) {
        const int row0 = mt * 128 + rank * 64;
        fence_async_smem();
        TRACE(22);
        tma2d_store(&maps.o64, sb + SM_FX, nt * 128, row0);
        tma2d_store(&maps.o64, sb + SM_FX + 8192, nt * 128 + 64, row0);
        tma2d_store(&maps.o32, sb + SM_FXN, 512 + 32 * nt, row0);
        bulk_commit();
        if (b == 0) atomicAdd(p.s->epoch, 1u);
        bulk_wait_read<0>();
        TRACE(7);
      }
    }
  }
}

typedef CUresult (*EncodeFn)(CUtensorMap*, CUtensorMapDataType, cuuint32_t, void*, const cuuint64_t*, const cuuint64_t*,
                             const cuuint32_t*, const cuuint32_t*, CUtensorMapInterleave, CUtensorMapSwizzle,
                             CUtensorMapL2promotion, CUtensorMapFloatOOBfill);

void make_map(EncodeFn enc, CUtensorMap* m, const void* base, int rank, const cuuint64_t* dims, const cuuint64_t* strides,
              const cuuint32_t* box, CUtensorMapSwizzle sw = CU_TENSOR_MAP_SWIZZLE_128B) {
  const cuuint32_t es[3] = {1, 1, 1};
  enc(m, CU_TENSOR_MAP_DATA_TYPE_BFLOAT16, rank, const_cast<void*>(base), dims, strides, box, es, CU_TENSOR_MAP_INTERLEAVE_NONE,
      sw, CU_TENSOR_MAP_L2_PROMOTION_NONE, CU_TENSOR_MAP_FLOAT_OOB_FILL_NONE);
}
void map2d(EncodeFn enc, CUtensorMap* m, const void* base, int cols, int rows, int bc, int br,
           CUtensorMapSwizzle sw = CU_TENSOR_MAP_SWIZZLE_128B) {
  const cuuint64_t d[2] = {(cuuint64_t)cols, (cuuint64_t)rows}, s[1] = {(cuuint64_t)cols * 2};
  const cuuint32_t bx[2] = {(cuuint32_t)bc, (cuuint32_t)br};
  make_map(enc, m, base, 2, d, s, bx, sw);
}
void map3d(EncodeFn enc, CUtensorMap* m, const void* base, int cols, int rows, int br, int nb) {
  const cuuint64_t d[3] = {64, (cuuint64_t)rows, (cuuint64_t)cols / 64}, s[2] = {(cuuint64_t)cols * 2, 128};
  const cuuint32_t bx[3] = {64, (cuuint32_t)br, (cuuint32_t)nb};
  make_map(enc, m, base, 3, d, s, bx);
}

}

extern "C" void kernel_launch(void* const* d_in, const int* in_sizes, int n_in, void* d_out, int out_size) {
  (void)in_sizes; (void)n_in; (void)out_size;
  static EncodeFn enc = nullptr;
  static Scratch* scr = nullptr;
  if (!enc) {
    void* fn = nullptr;
    cudaDriverEntryPointQueryResult qr;
    cudaGetDriverEntryPoint("cuTensorMapEncodeTiled", &fn, cudaEnableDefault, &qr);
    enc = (EncodeFn)fn;
    cudaGetSymbolAddress((void**)&scr, g_scratch);
    cudaFuncSetAttribute(fused_kernel, cudaFuncAttributeMaxDynamicSharedMemorySize, SM_TOTAL);
  }
  Params p;
  p.s = scr;
  p.x = (const uint16_t*)d_in[0];
  for (int i = 0; i < 6; i++) p.ssm[i] = (const uint16_t*)d_in[1 + i];
  p.logdt = (const uint16_t*)d_in[7]; p.dskip = (const uint16_t*)d_in[8];
  p.w1 = (const uint16_t*)d_in[10]; p.b1 = (const uint16_t*)d_in[11];
  p.w2 = (const uint16_t*)d_in[12]; p.b2 = (const uint16_t*)d_in[13];
  Maps m;
  map2d(enc, &m.x128, p.x, DM, SEQ, 64, 128);
  map2d(enc, &m.x64, p.x, DM, SEQ, 64, 64);
  map2d(enc, &m.x32, p.x, DM, SEQ, 32, 64);
  map3d(enc, &m.w1, p.w1, FF, DM, 32, 3);
  map2d(enc, &m.w1n, p.w1, FF, DM, 24, 32);
  map3d(enc, &m.w2, p.w2, DM, FF, 32, 2);
  map2d(enc, &m.w2n, p.w2, DM, FF, 32, 32);
  map2d(enc, &m.xt, scr->xnT, DM * 16, 128, 16, 129, CU_TENSOR_MAP_SWIZZLE_NONE);
  map2d(enc, &m.z128, scr->zT, SEQ, DM, 64, 128);
  map2d(enc, &m.z32, scr->zT, SEQ, DM, 64, 32);
  map2d(enc, &m.o64, d_out, DM, SEQ, 64, 64);
  map2d(enc, &m.o32, d_out, DM, SEQ, 32, 64);
  fused_kernel<<<NCTA, 512, SM_TOTAL>>>(p, m);
}
```
